```python
import torch

def _softmax(x, axis=-1):
    return torch.softmax(x, dim=axis)

def _gelu(x):
    return torch.nn.functional.gelu(x, approximate='tanh')

def _silu(x):
    return torch.nn.functional.silu(x)

def _sigmoid(x):
    return torch.sigmoid(x)

def _layernorm(x, axis=-1, eps=1e-05):
    m = x.mean(dim=axis, keepdim=True)
    v = x.var(dim=axis, keepdim=True, unbiased=False)
    return (x - m) / torch.sqrt(v + eps)

def _scatter_add(tgt, idx, src, axis=0):
    return tgt.clone().index_add_(axis, idx, src)

def _segment_sum(src, seg, n):
    out = torch.zeros((n,) + src.shape[1:], dtype=src.dtype)
    return out.index_add_(0, seg, src)

def _pad(x, pw):
    flat = tuple((v for pair in reversed(pw) for v in pair))
    return torch.nn.functional.pad(x, flat)
kernel_name = 'gated_mix__ssm_conv_s5__memory_aug_recurrent_mem_tr__prompt'

def setup_inputs():

    _w = lambda a: (lambda t: t.to(torch.bfloat16) if t.is_floating_point() else t)(torch.as_tensor(a))

    def _A_setup():
        B, S, D = (1, 2048, 448)
        P = D
        Lambda_re = -0.5 * (lambda _x: torch.exp(torch.as_tensor(_x)))((lambda *s: torch.randn(*s, dtype=torch.bfloat16) * 0.8)(P))
        Lambda_im = (lambda *s: torch.randn(*s, dtype=torch.bfloat16) * 0.8)(P) * 1.0
        B_re = (lambda *s: torch.randn(*s, dtype=torch.bfloat16) * 0.8)(P, D) * D ** (-0.5)
        B_im = (lambda *s: torch.randn(*s, dtype=torch.bfloat16) * 0.8)(P, D) * D ** (-0.5)
        C_re = (lambda *s: torch.randn(*s, dtype=torch.bfloat16) * 0.8)(D, P) * P ** (-0.5)
        C_im = (lambda *s: torch.randn(*s, dtype=torch.bfloat16) * 0.8)(D, P) * P ** (-0.5)
        log_dt = (lambda *s: torch.randn(*s, dtype=torch.bfloat16) * 0.8)(P) * 0.3 - 2.0
        Dskip = (lambda *s: torch.randn(*s, dtype=torch.bfloat16) * 0.8)(D)
        return {'x': _w((lambda *s: torch.randn(*s, dtype=torch.bfloat16) * 0.05)(B, S, D)), 'Lambda_re': _w(Lambda_re), 'Lambda_im': _w(Lambda_im), 'B_re': _w(B_re), 'B_im': _w(B_im), 'C_re': _w(C_re), 'C_im': _w(C_im), 'log_dt': _w(log_dt), 'Dskip': _w(Dskip)}
    _A_in = _A_setup()

    def _B_setup():
        B, S, Dm = (1, 2048, 448)
        H, Dh = (16, 256)
        M, seg = (8, 32)
        seg = min(seg, S)
        S = S // seg * seg
        return {'x': _w((lambda *s: torch.randn(*s, dtype=torch.bfloat16) * 0.05)(B, S, Dm)), 'mem0': _w((lambda *s: torch.randn(*s, dtype=torch.bfloat16) * 0.8)(B, M, Dm)), 'Wq': _w((lambda *s: torch.randn(*s, dtype=torch.bfloat16) * 3.2)(Dm, H, Dh) * Dm ** (-0.5)), 'Wk': _w((lambda *s: torch.randn(*s, dtype=torch.bfloat16) * 3.2)(Dm, H, Dh) * Dm ** (-0.5)), 'Wv': _w((lambda *s: torch.randn(*s, dtype=torch.bfloat16) * 0.8)(Dm, H, Dh) * Dm ** (-0.5)), 'Wo': _w((lambda *s: torch.randn(*s, dtype=torch.bfloat16) * 0.8)(H, Dh, Dm) * (H * Dh) ** (-0.5)), 'seg_len': seg}
    _B_in = _B_setup()
    return {'A_x': _A_in['x'], 'A_Lambda_re': _A_in['Lambda_re'], 'A_Lambda_im': _A_in['Lambda_im'], 'A_B_re': _A_in['B_re'], 'A_B_im': _A_in['B_im'], 'A_C_re': _A_in['C_re'], 'A_C_im': _A_in['C_im'], 'A_log_dt': _A_in['log_dt'], 'A_Dskip': _A_in['Dskip'], 'B_x': _B_in['x'], 'B_mem0': _B_in['mem0'], 'B_Wq': _B_in['Wq'], 'B_Wk': _B_in['Wk'], 'B_Wv': _B_in['Wv'], 'B_Wo': _B_in['Wo'], 'B_seg_len': _B_in['seg_len'], 'gate_w': _w((lambda *s: torch.randn(*s, dtype=torch.bfloat16) * 0.05)(448) * 16.0)}

def reference(A_x, A_Lambda_re, A_Lambda_im, A_B_re, A_B_im, A_C_re, A_C_im, A_log_dt, A_Dskip, B_x, B_mem0, B_Wq, B_Wk, B_Wv, B_Wo, B_seg_len, gate_w):

    def _A_ref(x, Lambda_re, Lambda_im, B_re, B_im, C_re, C_im, log_dt, Dskip):
        Bsz, L, H = x.shape
        Lam = Lambda_re + 1j * Lambda_im
        Bmat = B_re + 1j * B_im
        Cmat = C_re + 1j * C_im
        dt = torch.exp(log_dt)
        Lam_bar = torch.exp(dt * Lam)
        B_bar = ((Lam_bar - 1.0) / Lam)[:, None] * Bmat
        Bu = torch.einsum('bld,pd->blp', x + 0j, B_bar)
        h = torch.zeros_like(Bu[:, 0, :])
        hs = []
        for t in range(L):
            h = Lam_bar[None, :] * h + Bu[:, t, :]
            hs.append(h)
        hseq = torch.stack(hs, 1)
        y = 2.0 * torch.einsum('blp,dp->bld', hseq, Cmat).real + x * Dskip[None, None, :]
        return y

    def _B_ref(x, mem0, Wq, Wk, Wv, Wo, seg_len):
        B, S, Dm = x.shape
        H, Dh = (Wq.shape[1], Wq.shape[2])
        M = mem0.shape[1]
        scale = Dh ** (-0.5)
        n_seg = S // seg_len
        L = M + seg_len
        idx = torch.arange(L)
        mask = (idx[:, None] < M) | (idx[:, None] >= idx[None, :])
        mem = mem0
        outs = []
        for s in range(n_seg):
            xs = x[:, s * seg_len:(s + 1) * seg_len, :].clone()
            h = torch.concatenate([mem, xs], axis=1)
            q = torch.einsum('btd,dhe->bhte', h, Wq)
            k = torch.einsum('btd,dhe->bhte', h, Wk)
            v = torch.einsum('btd,dhe->bhte', h, Wv)
            scores = torch.einsum('bhqe,bhke->bhqk', q, k) * scale
            scores = torch.where(mask[None, None], scores, -1000000000.0)
            p = _softmax(scores, axis=-1)
            o = torch.einsum('bhqk,bhke->bhqe', p, v)
            o = torch.einsum('bhte,hed->btd', o, Wo)
            mem = o[:, :M, :].clone()
            outs.append(o[:, M:, :])
        return torch.concatenate(outs, axis=1)
    x = A_x
    g = _sigmoid((x * gate_w).sum(-1, keepdims=True))
    a = _A_ref(x, A_Lambda_re, A_Lambda_im, A_B_re, A_B_im, A_C_re, A_C_im, A_log_dt, A_Dskip)
    b = _B_ref(x, B_mem0, B_Wq, B_Wk, B_Wv, B_Wo, B_seg_len)
    return g * a + (1 - g) * b
```

```cpp
#define SIMPLE_POLL
#define NOTS
#include <cuda_runtime.h>
#include <cuda_bf16.h>
#include <cuda_fp16.h>
#include <cuda.h>
#include <stdint.h>

typedef __nv_bfloat16 bf16;

constexpr int D = 448, NH = 16, MEM = 8, NSEG = 64, NTOK = 2048;
constexpr int CL = 6;
constexpr float LOG2E = 1.4426950408889634f;

__device__ __align__(1024) bf16  g_At[NH * D * D];
__device__ __align__(1024) uint4 g_AtF[NH * 28 * 28 * 32];
__device__ __align__(1024) uint4 g_UtF[NH * 28 * 28 * 32];
__device__ __align__(1024) float4 g_acc[NSEG * CL * 80 * 3];
__device__ __align__(1024) uint2 g_vfrag[NSEG * 28 * NH * 5 * 32];
__device__ __align__(1024) uint2 g_pfrag[NSEG * 2 * NH * 5 * 32];
__device__ __align__(1024) bf16  g_mem[NSEG * MEM * D];
__device__ __align__(1024) bf16  g_hT[2 * D * NTOK];
__device__ float g_gate[NTOK], g_omg[NTOK];
__device__ int   g_err;
__device__ uint32_t g_sink;
__device__ int   g_q[4], g_cnt_s5a[16], g_mem_ready[NSEG], g_cnt_tx[NSEG], g_cnt_v[NSEG], g_cnt_ga[16];
__device__ long long g_dbg[4096];

__device__ __forceinline__ uint32_t smem_u32(const void* p) { return (uint32_t)__cvta_generic_to_shared(p); }
__device__ __forceinline__ uint32_t mapa(uint32_t a, uint32_t r) { uint32_t o; asm volatile("mapa.shared::cluster.u32 %0, %1, %2;" : "=r"(o) : "r"(a), "r"(r)); return o; }
__device__ __forceinline__ void mbar_init(uint32_t a, uint32_t c) { asm volatile("mbarrier.init.shared::cta.b64 [%0], %1;" :: "r"(a), "r"(c)); }
__device__ __forceinline__ void mbar_expect_tx(uint32_t a, uint32_t b) { asm volatile("mbarrier.arrive.expect_tx.shared::cta.b64 _, [%0], %1;" :: "r"(a), "r"(b) : "memory"); }
__device__ __forceinline__ void mbar_arrive(uint32_t a) { asm volatile("mbarrier.arrive.shared::cta.b64 _, [%0];" :: "r"(a) : "memory"); }
__device__ __forceinline__ bool mbar_try(uint32_t a, uint32_t par) {
    uint32_t ok;
    asm volatile("{\n.reg .pred p;\nmbarrier.try_wait.parity.shared::cta.b64 p, [%1], %2;\nselp.u32 %0, 1, 0, p;\n}" : "=r"(ok) : "r"(a), "r"(par) : "memory");
    return ok;
}
__device__ __forceinline__ void mbar_wait(uint32_t a, uint32_t par) {
    int it = 0;
    while (!mbar_try(a, par)) { if (++it > 400000) { atomicAdd(&g_err, 1); break; } }
}
__device__ __forceinline__ void st_async_v4(uint32_t dst, uint4 v, uint32_t mbar) {
    asm volatile("st.async.weak.shared::cluster.mbarrier::complete_tx::bytes.v4.b32 [%0], {%1,%2,%3,%4}, [%5];" :: "r"(dst), "r"(v.x), "r"(v.y), "r"(v.z), "r"(v.w), "r"(mbar) : "memory");
}
__device__ __forceinline__ float4 ld_relaxed_f4(const float4* p) {
    float4 v;
    asm volatile("ld.relaxed.gpu.global.v4.f32 {%0,%1,%2,%3}, [%4];" : "=f"(v.x), "=f"(v.y), "=f"(v.z), "=f"(v.w) : "l"(p) : "memory");
    return v;
}
__device__ __forceinline__ void red_f4(float4* p, float a, float b, float c, float d) {
    asm volatile("red.relaxed.gpu.global.add.v4.f32 [%0], {%1,%2,%3,%4};" :: "l"(p), "f"(a), "f"(b), "f"(c), "f"(d) : "memory");
}
__device__ __forceinline__ void mma_nv(float* c, uint32_t a0, uint32_t a1, uint32_t a2, uint32_t a3, uint32_t b0, uint32_t b1) {
    asm("mma.sync.aligned.m16n8k16.row.col.f32.bf16.bf16.f32 {%0,%1,%2,%3}, {%4,%5,%6,%7}, {%8,%9}, {%0,%1,%2,%3};"
        : "+f"(c[0]), "+f"(c[1]), "+f"(c[2]), "+f"(c[3]) : "r"(a0), "r"(a1), "r"(a2), "r"(a3), "r"(b0), "r"(b1));
}
__device__ __forceinline__ void mma8_nv(float* c, uint32_t a0, uint32_t a1, uint32_t b0) {
    asm("mma.sync.aligned.m16n8k8.row.col.f32.bf16.bf16.f32 {%0,%1,%2,%3}, {%4,%5}, {%6}, {%0,%1,%2,%3};"
        : "+f"(c[0]), "+f"(c[1]), "+f"(c[2]), "+f"(c[3]) : "r"(a0), "r"(a1), "r"(b0));
}
__device__ __forceinline__ void ldsm4(uint32_t* r, uint32_t a) {
    asm volatile("ldmatrix.sync.aligned.m8n8.x4.shared.b16 {%0,%1,%2,%3}, [%4];" : "=r"(r[0]), "=r"(r[1]), "=r"(r[2]), "=r"(r[3]) : "r"(a));
}
__device__ __forceinline__ uint32_t movm_nv(uint32_t x) { uint32_t y; asm("movmatrix.sync.aligned.m8n8.trans.b16 %0, %1;" : "=r"(y) : "r"(x)); return y; }
__device__ __forceinline__ uint32_t pack_bf16(float lo, float hi) { uint32_t r; asm("cvt.rn.bf16x2.f32 %0, %1, %2;" : "=r"(r) : "f"(hi), "f"(lo)); return r; }
__device__ __forceinline__ uint32_t pack_f16_sat(float lo, float hi) { uint32_t r; asm("cvt.rn.satfinite.f16x2.f32 %0, %1, %2;" : "=r"(r) : "f"(hi), "f"(lo)); return r; }
__device__ __forceinline__ float bf_lo(uint32_t x) { return __uint_as_float(x << 16); }
__device__ __forceinline__ float bf_hi(uint32_t x) { return __uint_as_float(x & 0xffff0000u); }
__device__ __forceinline__ float bfr(float x) { return __bfloat162float(__float2bfloat16_rn(x)); }
__device__ __forceinline__ float ex2(float x) { float y; asm("ex2.approx.ftz.f32 %0, %1;" : "=f"(y) : "f"(x)); return y; }
__device__ __forceinline__ void bar_sync(int id, int n) { asm volatile("bar.sync %0, %1;" :: "r"(id), "r"(n) : "memory"); }
__device__ __forceinline__ void bar_arrive(int id, int n) { asm volatile("bar.arrive %0, %1;" :: "r"(id), "r"(n) : "memory"); }
__device__ __forceinline__ uint2 ls64(uint32_t a) { uint2 v; asm volatile("ld.shared.v2.u32 {%0,%1}, [%2];" : "=r"(v.x), "=r"(v.y) : "r"(a)); return v; }
__device__ __forceinline__ uint4 ls128(uint32_t a) { uint4 v; asm volatile("ld.shared.v4.u32 {%0,%1,%2,%3}, [%4];" : "=r"(v.x), "=r"(v.y), "=r"(v.z), "=r"(v.w) : "r"(a)); return v; }
__device__ __forceinline__ float4 lf128(uint32_t a) { float4 v; asm volatile("ld.shared.v4.f32 {%0,%1,%2,%3}, [%4];" : "=f"(v.x), "=f"(v.y), "=f"(v.z), "=f"(v.w) : "r"(a)); return v; }
__device__ __forceinline__ float2 lf64(uint32_t a) { float2 v; asm volatile("ld.shared.v2.f32 {%0,%1}, [%2];" : "=f"(v.x), "=f"(v.y) : "r"(a)); return v; }
__device__ __forceinline__ void ss128(uint32_t a, uint4 v) { asm volatile("st.shared.v4.u32 [%0], {%1,%2,%3,%4};" :: "r"(a), "r"(v.x), "r"(v.y), "r"(v.z), "r"(v.w)); }
__device__ __forceinline__ void sf128(uint32_t a, float x, float y, float z, float w) { asm volatile("st.shared.v4.f32 [%0], {%1,%2,%3,%4};" :: "r"(a), "f"(x), "f"(y), "f"(z), "f"(w)); }
__device__ __forceinline__ void sf64(uint32_t a, float x, float y) { asm volatile("st.shared.v2.f32 [%0], {%1,%2};" :: "r"(a), "f"(x), "f"(y)); }
__device__ __forceinline__ void sf32(uint32_t a, float x) { asm volatile("st.shared.f32 [%0], %1;" :: "r"(a), "f"(x)); }
__device__ __forceinline__ void wg_fence() { asm volatile("wgmma.fence.sync.aligned;" ::: "memory"); }
__device__ __forceinline__ void wg_commit() { asm volatile("wgmma.commit_group.sync.aligned;" ::: "memory"); }
__device__ __forceinline__ void wg_wait0() { asm volatile("wgmma.wait_group.sync.aligned 0;" ::: "memory"); }
__device__ __forceinline__ void wg_wait1() { asm volatile("wgmma.wait_group.sync.aligned 1;" ::: "memory"); }
__device__ __forceinline__ uint64_t desc_sw128(uint32_t addr) { return (uint64_t)((addr & 0x3FFFF) >> 4) | (1ull << 16) | (64ull << 32) | (1ull << 62); }
__device__ __forceinline__ uint64_t opaque64(uint64_t x) { uint64_t y; asm volatile("mov.b64 %0, %1;" : "=l"(y) : "l"(x)); return y; }
__device__ __forceinline__ void tma_2d(uint32_t dst, const CUtensorMap* m, int c0, int c1, uint32_t mbar) {
    asm volatile("cp.async.bulk.tensor.2d.shared::cta.global.mbarrier::complete_tx::bytes [%0], [%1, {%3, %4}], [%2];"
        :: "r"(dst), "l"(m), "r"(mbar), "r"(c0), "r"(c1) : "memory");
}
__device__ __forceinline__ void wg_n224_ss(float* d, uint64_t da, uint64_t db, int sd) {
    asm volatile("{\n.reg .pred p;\nsetp.ne.b32 p, %114, 0;\n"
        "wgmma.mma_async.sync.aligned.m64n224k16.f32.bf16.bf16 {%0,%1,%2,%3,%4,%5,%6,%7,%8,%9,%10,%11,%12,%13,%14,%15,%16,%17,%18,%19,%20,%21,%22,%23,%24,%25,%26,%27,%28,%29,%30,%31,%32,%33,%34,%35,%36,%37,%38,%39,%40,%41,%42,%43,%44,%45,%46,%47,%48,%49,%50,%51,%52,%53,%54,%55,%56,%57,%58,%59,%60,%61,%62,%63,%64,%65,%66,%67,%68,%69,%70,%71,%72,%73,%74,%75,%76,%77,%78,%79,%80,%81,%82,%83,%84,%85,%86,%87,%88,%89,%90,%91,%92,%93,%94,%95,%96,%97,%98,%99,%100,%101,%102,%103,%104,%105,%106,%107,%108,%109,%110,%111}, %112, %113, p, 1, 1, 0, 0;\n}\n"
        : "+f"(d[0]), "+f"(d[1]), "+f"(d[2]), "+f"(d[3]), "+f"(d[4]), "+f"(d[5]), "+f"(d[6]), "+f"(d[7]), "+f"(d[8]), "+f"(d[9]), "+f"(d[10]), "+f"(d[11]), "+f"(d[12]), "+f"(d[13]), "+f"(d[14]), "+f"(d[15]), "+f"(d[16]), "+f"(d[17]), "+f"(d[18]), "+f"(d[19]), "+f"(d[20]), "+f"(d[21]), "+f"(d[22]), "+f"(d[23]), "+f"(d[24]), "+f"(d[25]), "+f"(d[26]), "+f"(d[27]), "+f"(d[28]), "+f"(d[29]), "+f"(d[30]), "+f"(d[31]), "+f"(d[32]), "+f"(d[33]), "+f"(d[34]), "+f"(d[35]), "+f"(d[36]), "+f"(d[37]), "+f"(d[38]), "+f"(d[39]), "+f"(d[40]), "+f"(d[41]), "+f"(d[42]), "+f"(d[43]), "+f"(d[44]), "+f"(d[45]), "+f"(d[46]), "+f"(d[47]), "+f"(d[48]), "+f"(d[49]), "+f"(d[50]), "+f"(d[51]), "+f"(d[52]), "+f"(d[53]), "+f"(d[54]), "+f"(d[55]), "+f"(d[56]), "+f"(d[57]), "+f"(d[58]), "+f"(d[59]), "+f"(d[60]), "+f"(d[61]), "+f"(d[62]), "+f"(d[63]), "+f"(d[64]), "+f"(d[65]), "+f"(d[66]), "+f"(d[67]), "+f"(d[68]), "+f"(d[69]), "+f"(d[70]), "+f"(d[71]), "+f"(d[72]), "+f"(d[73]), "+f"(d[74]), "+f"(d[75]), "+f"(d[76]), "+f"(d[77]), "+f"(d[78]), "+f"(d[79]), "+f"(d[80]), "+f"(d[81]), "+f"(d[82]), "+f"(d[83]), "+f"(d[84]), "+f"(d[85]), "+f"(d[86]), "+f"(d[87]), "+f"(d[88]), "+f"(d[89]), "+f"(d[90]), "+f"(d[91]), "+f"(d[92]), "+f"(d[93]), "+f"(d[94]), "+f"(d[95]), "+f"(d[96]), "+f"(d[97]), "+f"(d[98]), "+f"(d[99]), "+f"(d[100]), "+f"(d[101]), "+f"(d[102]), "+f"(d[103]), "+f"(d[104]), "+f"(d[105]), "+f"(d[106]), "+f"(d[107]), "+f"(d[108]), "+f"(d[109]), "+f"(d[110]), "+f"(d[111])
        : "l"(da), "l"(db), "r"(sd));
}
__device__ __forceinline__ void wg_n224_ss_ta(float* d, uint64_t da, uint64_t db, int sd) {
    asm volatile("{\n.reg .pred p;\nsetp.ne.b32 p, %114, 0;\n"
        "wgmma.mma_async.sync.aligned.m64n224k16.f32.bf16.bf16 {%0,%1,%2,%3,%4,%5,%6,%7,%8,%9,%10,%11,%12,%13,%14,%15,%16,%17,%18,%19,%20,%21,%22,%23,%24,%25,%26,%27,%28,%29,%30,%31,%32,%33,%34,%35,%36,%37,%38,%39,%40,%41,%42,%43,%44,%45,%46,%47,%48,%49,%50,%51,%52,%53,%54,%55,%56,%57,%58,%59,%60,%61,%62,%63,%64,%65,%66,%67,%68,%69,%70,%71,%72,%73,%74,%75,%76,%77,%78,%79,%80,%81,%82,%83,%84,%85,%86,%87,%88,%89,%90,%91,%92,%93,%94,%95,%96,%97,%98,%99,%100,%101,%102,%103,%104,%105,%106,%107,%108,%109,%110,%111}, %112, %113, p, 1, 1, 1, 0;\n}\n"
        : "+f"(d[0]), "+f"(d[1]), "+f"(d[2]), "+f"(d[3]), "+f"(d[4]), "+f"(d[5]), "+f"(d[6]), "+f"(d[7]), "+f"(d[8]), "+f"(d[9]), "+f"(d[10]), "+f"(d[11]), "+f"(d[12]), "+f"(d[13]), "+f"(d[14]), "+f"(d[15]), "+f"(d[16]), "+f"(d[17]), "+f"(d[18]), "+f"(d[19]), "+f"(d[20]), "+f"(d[21]), "+f"(d[22]), "+f"(d[23]), "+f"(d[24]), "+f"(d[25]), "+f"(d[26]), "+f"(d[27]), "+f"(d[28]), "+f"(d[29]), "+f"(d[30]), "+f"(d[31]), "+f"(d[32]), "+f"(d[33]), "+f"(d[34]), "+f"(d[35]), "+f"(d[36]), "+f"(d[37]), "+f"(d[38]), "+f"(d[39]), "+f"(d[40]), "+f"(d[41]), "+f"(d[42]), "+f"(d[43]), "+f"(d[44]), "+f"(d[45]), "+f"(d[46]), "+f"(d[47]), "+f"(d[48]), "+f"(d[49]), "+f"(d[50]), "+f"(d[51]), "+f"(d[52]), "+f"(d[53]), "+f"(d[54]), "+f"(d[55]), "+f"(d[56]), "+f"(d[57]), "+f"(d[58]), "+f"(d[59]), "+f"(d[60]), "+f"(d[61]), "+f"(d[62]), "+f"(d[63]), "+f"(d[64]), "+f"(d[65]), "+f"(d[66]), "+f"(d[67]), "+f"(d[68]), "+f"(d[69]), "+f"(d[70]), "+f"(d[71]), "+f"(d[72]), "+f"(d[73]), "+f"(d[74]), "+f"(d[75]), "+f"(d[76]), "+f"(d[77]), "+f"(d[78]), "+f"(d[79]), "+f"(d[80]), "+f"(d[81]), "+f"(d[82]), "+f"(d[83]), "+f"(d[84]), "+f"(d[85]), "+f"(d[86]), "+f"(d[87]), "+f"(d[88]), "+f"(d[89]), "+f"(d[90]), "+f"(d[91]), "+f"(d[92]), "+f"(d[93]), "+f"(d[94]), "+f"(d[95]), "+f"(d[96]), "+f"(d[97]), "+f"(d[98]), "+f"(d[99]), "+f"(d[100]), "+f"(d[101]), "+f"(d[102]), "+f"(d[103]), "+f"(d[104]), "+f"(d[105]), "+f"(d[106]), "+f"(d[107]), "+f"(d[108]), "+f"(d[109]), "+f"(d[110]), "+f"(d[111])
        : "l"(da), "l"(db), "r"(sd));
}
__device__ __forceinline__ void wg_n224_ss_ta_neg(float* d, uint64_t da, uint64_t db, int sd) {
    asm volatile("{\n.reg .pred p;\nsetp.ne.b32 p, %114, 0;\n"
        "wgmma.mma_async.sync.aligned.m64n224k16.f32.bf16.bf16 {%0,%1,%2,%3,%4,%5,%6,%7,%8,%9,%10,%11,%12,%13,%14,%15,%16,%17,%18,%19,%20,%21,%22,%23,%24,%25,%26,%27,%28,%29,%30,%31,%32,%33,%34,%35,%36,%37,%38,%39,%40,%41,%42,%43,%44,%45,%46,%47,%48,%49,%50,%51,%52,%53,%54,%55,%56,%57,%58,%59,%60,%61,%62,%63,%64,%65,%66,%67,%68,%69,%70,%71,%72,%73,%74,%75,%76,%77,%78,%79,%80,%81,%82,%83,%84,%85,%86,%87,%88,%89,%90,%91,%92,%93,%94,%95,%96,%97,%98,%99,%100,%101,%102,%103,%104,%105,%106,%107,%108,%109,%110,%111}, %112, %113, p, 1, -1, 1, 0;\n}\n"
        : "+f"(d[0]), "+f"(d[1]), "+f"(d[2]), "+f"(d[3]), "+f"(d[4]), "+f"(d[5]), "+f"(d[6]), "+f"(d[7]), "+f"(d[8]), "+f"(d[9]), "+f"(d[10]), "+f"(d[11]), "+f"(d[12]), "+f"(d[13]), "+f"(d[14]), "+f"(d[15]), "+f"(d[16]), "+f"(d[17]), "+f"(d[18]), "+f"(d[19]), "+f"(d[20]), "+f"(d[21]), "+f"(d[22]), "+f"(d[23]), "+f"(d[24]), "+f"(d[25]), "+f"(d[26]), "+f"(d[27]), "+f"(d[28]), "+f"(d[29]), "+f"(d[30]), "+f"(d[31]), "+f"(d[32]), "+f"(d[33]), "+f"(d[34]), "+f"(d[35]), "+f"(d[36]), "+f"(d[37]), "+f"(d[38]), "+f"(d[39]), "+f"(d[40]), "+f"(d[41]), "+f"(d[42]), "+f"(d[43]), "+f"(d[44]), "+f"(d[45]), "+f"(d[46]), "+f"(d[47]), "+f"(d[48]), "+f"(d[49]), "+f"(d[50]), "+f"(d[51]), "+f"(d[52]), "+f"(d[53]), "+f"(d[54]), "+f"(d[55]), "+f"(d[56]), "+f"(d[57]), "+f"(d[58]), "+f"(d[59]), "+f"(d[60]), "+f"(d[61]), "+f"(d[62]), "+f"(d[63]), "+f"(d[64]), "+f"(d[65]), "+f"(d[66]), "+f"(d[67]), "+f"(d[68]), "+f"(d[69]), "+f"(d[70]), "+f"(d[71]), "+f"(d[72]), "+f"(d[73]), "+f"(d[74]), "+f"(d[75]), "+f"(d[76]), "+f"(d[77]), "+f"(d[78]), "+f"(d[79]), "+f"(d[80]), "+f"(d[81]), "+f"(d[82]), "+f"(d[83]), "+f"(d[84]), "+f"(d[85]), "+f"(d[86]), "+f"(d[87]), "+f"(d[88]), "+f"(d[89]), "+f"(d[90]), "+f"(d[91]), "+f"(d[92]), "+f"(d[93]), "+f"(d[94]), "+f"(d[95]), "+f"(d[96]), "+f"(d[97]), "+f"(d[98]), "+f"(d[99]), "+f"(d[100]), "+f"(d[101]), "+f"(d[102]), "+f"(d[103]), "+f"(d[104]), "+f"(d[105]), "+f"(d[106]), "+f"(d[107]), "+f"(d[108]), "+f"(d[109]), "+f"(d[110]), "+f"(d[111])
        : "l"(da), "l"(db), "r"(sd));
}
__device__ __forceinline__ void wg_n128_ss(float* d, uint64_t da, uint64_t db, int sd) {
    asm volatile("{\n.reg .pred p;\nsetp.ne.b32 p, %66, 0;\n"
        "wgmma.mma_async.sync.aligned.m64n128k16.f32.bf16.bf16 {%0,%1,%2,%3,%4,%5,%6,%7,%8,%9,%10,%11,%12,%13,%14,%15,%16,%17,%18,%19,%20,%21,%22,%23,%24,%25,%26,%27,%28,%29,%30,%31,%32,%33,%34,%35,%36,%37,%38,%39,%40,%41,%42,%43,%44,%45,%46,%47,%48,%49,%50,%51,%52,%53,%54,%55,%56,%57,%58,%59,%60,%61,%62,%63}, %64, %65, p, 1, 1, 0, 0;\n}\n"
        : "+f"(d[0]), "+f"(d[1]), "+f"(d[2]), "+f"(d[3]), "+f"(d[4]), "+f"(d[5]), "+f"(d[6]), "+f"(d[7]), "+f"(d[8]), "+f"(d[9]), "+f"(d[10]), "+f"(d[11]), "+f"(d[12]), "+f"(d[13]), "+f"(d[14]), "+f"(d[15]), "+f"(d[16]), "+f"(d[17]), "+f"(d[18]), "+f"(d[19]), "+f"(d[20]), "+f"(d[21]), "+f"(d[22]), "+f"(d[23]), "+f"(d[24]), "+f"(d[25]), "+f"(d[26]), "+f"(d[27]), "+f"(d[28]), "+f"(d[29]), "+f"(d[30]), "+f"(d[31]), "+f"(d[32]), "+f"(d[33]), "+f"(d[34]), "+f"(d[35]), "+f"(d[36]), "+f"(d[37]), "+f"(d[38]), "+f"(d[39]), "+f"(d[40]), "+f"(d[41]), "+f"(d[42]), "+f"(d[43]), "+f"(d[44]), "+f"(d[45]), "+f"(d[46]), "+f"(d[47]), "+f"(d[48]), "+f"(d[49]), "+f"(d[50]), "+f"(d[51]), "+f"(d[52]), "+f"(d[53]), "+f"(d[54]), "+f"(d[55]), "+f"(d[56]), "+f"(d[57]), "+f"(d[58]), "+f"(d[59]), "+f"(d[60]), "+f"(d[61]), "+f"(d[62]), "+f"(d[63])
        : "l"(da), "l"(db), "r"(sd));
}
__device__ __forceinline__ void wg_n64_rs(float* d, uint32_t a0, uint32_t a1, uint32_t a2, uint32_t a3, uint64_t db, int sd) {
    asm volatile("{\n.reg .pred p;\nsetp.ne.b32 p, %37, 0;\n"
        "wgmma.mma_async.sync.aligned.m64n64k16.f32.bf16.bf16 {%0,%1,%2,%3,%4,%5,%6,%7,%8,%9,%10,%11,%12,%13,%14,%15,%16,%17,%18,%19,%20,%21,%22,%23,%24,%25,%26,%27,%28,%29,%30,%31}, {%32,%33,%34,%35}, %36, p, 1, 1, 0;\n}\n"
        : "+f"(d[0]), "+f"(d[1]), "+f"(d[2]), "+f"(d[3]), "+f"(d[4]), "+f"(d[5]), "+f"(d[6]), "+f"(d[7]), "+f"(d[8]), "+f"(d[9]), "+f"(d[10]), "+f"(d[11]), "+f"(d[12]), "+f"(d[13]), "+f"(d[14]), "+f"(d[15]), "+f"(d[16]), "+f"(d[17]), "+f"(d[18]), "+f"(d[19]), "+f"(d[20]), "+f"(d[21]), "+f"(d[22]), "+f"(d[23]), "+f"(d[24]), "+f"(d[25]), "+f"(d[26]), "+f"(d[27]), "+f"(d[28]), "+f"(d[29]), "+f"(d[30]), "+f"(d[31])
        : "r"(a0), "r"(a1), "r"(a2), "r"(a3), "l"(db), "r"(sd));
}
__device__ __forceinline__ void wg_n16_rs(float* d, uint32_t a0, uint32_t a1, uint32_t a2, uint32_t a3, uint64_t db, int sd) {
    asm volatile("{\n.reg .pred p;\nsetp.ne.b32 p, %13, 0;\n"
        "wgmma.mma_async.sync.aligned.m64n16k16.f32.bf16.bf16 {%0,%1,%2,%3,%4,%5,%6,%7}, {%8,%9,%10,%11}, %12, p, 1, 1, 0;\n}\n"
        : "+f"(d[0]), "+f"(d[1]), "+f"(d[2]), "+f"(d[3]), "+f"(d[4]), "+f"(d[5]), "+f"(d[6]), "+f"(d[7])
        : "r"(a0), "r"(a1), "r"(a2), "r"(a3), "l"(db), "r"(sd));
}
__device__ __forceinline__ void wg_n32_rs(float* d, uint32_t a0, uint32_t a1, uint32_t a2, uint32_t a3, uint64_t db, int sd) {
    asm volatile("{\n.reg .pred p;\nsetp.ne.b32 p, %21, 0;\n"
        "wgmma.mma_async.sync.aligned.m64n32k16.f32.bf16.bf16 {%0,%1,%2,%3,%4,%5,%6,%7,%8,%9,%10,%11,%12,%13,%14,%15}, {%16,%17,%18,%19}, %20, p, 1, 1, 0;\n}\n"
        : "+f"(d[0]), "+f"(d[1]), "+f"(d[2]), "+f"(d[3]), "+f"(d[4]), "+f"(d[5]), "+f"(d[6]), "+f"(d[7]), "+f"(d[8]), "+f"(d[9]), "+f"(d[10]), "+f"(d[11]), "+f"(d[12]), "+f"(d[13]), "+f"(d[14]), "+f"(d[15])
        : "r"(a0), "r"(a1), "r"(a2), "r"(a3), "l"(db), "r"(sd));
}
__device__ __forceinline__ void wg_n8_rs(float* d, uint32_t a0, uint32_t a1, uint32_t a2, uint32_t a3, uint64_t db, int sd) {
    asm volatile("{\n.reg .pred p;\nsetp.ne.b32 p, %9, 0;\n"
        "wgmma.mma_async.sync.aligned.m64n8k16.f32.bf16.bf16 {%0,%1,%2,%3}, {%4,%5,%6,%7}, %8, p, 1, 1, 0;\n}\n"
        : "+f"(d[0]), "+f"(d[1]), "+f"(d[2]), "+f"(d[3])
        : "r"(a0), "r"(a1), "r"(a2), "r"(a3), "l"(db), "r"(sd));
}
__device__ __forceinline__ void wg_n64_ss_tb(float* d, uint64_t da, uint64_t db, int sd) {
    asm volatile("{\n.reg .pred p;\nsetp.ne.b32 p, %34, 0;\n"
        "wgmma.mma_async.sync.aligned.m64n64k16.f32.bf16.bf16 {%0,%1,%2,%3,%4,%5,%6,%7,%8,%9,%10,%11,%12,%13,%14,%15,%16,%17,%18,%19,%20,%21,%22,%23,%24,%25,%26,%27,%28,%29,%30,%31}, %32, %33, p, 1, 1, 0, 1;\n}\n"
        : "+f"(d[0]), "+f"(d[1]), "+f"(d[2]), "+f"(d[3]), "+f"(d[4]), "+f"(d[5]), "+f"(d[6]), "+f"(d[7]), "+f"(d[8]), "+f"(d[9]), "+f"(d[10]), "+f"(d[11]), "+f"(d[12]), "+f"(d[13]), "+f"(d[14]), "+f"(d[15]), "+f"(d[16]), "+f"(d[17]), "+f"(d[18]), "+f"(d[19]), "+f"(d[20]), "+f"(d[21]), "+f"(d[22]), "+f"(d[23]), "+f"(d[24]), "+f"(d[25]), "+f"(d[26]), "+f"(d[27]), "+f"(d[28]), "+f"(d[29]), "+f"(d[30]), "+f"(d[31])
        : "l"(da), "l"(db), "r"(sd));
}
__device__ __forceinline__ void wg_n16_ss_tb(float* d, uint64_t da, uint64_t db, int sd) {
    asm volatile("{\n.reg .pred p;\nsetp.ne.b32 p, %10, 0;\n"
        "wgmma.mma_async.sync.aligned.m64n16k16.f32.bf16.bf16 {%0,%1,%2,%3,%4,%5,%6,%7}, %8, %9, p, 1, 1, 0, 1;\n}\n"
        : "+f"(d[0]), "+f"(d[1]), "+f"(d[2]), "+f"(d[3]), "+f"(d[4]), "+f"(d[5]), "+f"(d[6]), "+f"(d[7])
        : "l"(da), "l"(db), "r"(sd));
}
constexpr int PREP_THREADS = 384;
constexpr uint32_t PP_B = 0, PP_A = 4 * 28672, PP_MB = PP_A + 3 * 32768;
constexpr uint32_t PREP_SMEM = PP_MB + 128;
constexpr int PREP_ITEMS = 128;
__global__ void __launch_bounds__(PREP_THREADS, 1)
prep_kernel(const __grid_constant__ CUtensorMap tmWk, const __grid_constant__ CUtensorMap tmWq, const __grid_constant__ CUtensorMap tmWv,
            const __grid_constant__ CUtensorMap tmWo, const __grid_constant__ CUtensorMap tmAtS,
            const bf16* __restrict__ Ax, const bf16* __restrict__ gate_w, const bf16* __restrict__ mem0,
            const bf16* __restrict__ Wq, const bf16* __restrict__ Wk, const bf16* __restrict__ Wv, const bf16* __restrict__ Wo)
{
    extern __shared__ __align__(1024) uint8_t smem_raw[];
    const int tid = threadIdx.x, warp = __shfl_sync(0xffffffffu, (int)threadIdx.x >> 5, 0), lane = tid & 31;
    asm volatile("griddepcontrol.launch_dependents;" ::: "memory");
    const int nh = blockIdx.x & 1, mh = (blockIdx.x >> 1) & 1, h = (blockIdx.x >> 2) & 15, z = blockIdx.x >> 6;
    const int nmt = mh == 0 ? 4 : 3;
    const uint32_t sb = smem_u32(smem_raw);
    const uint32_t mbB = sb + PP_MB, mbA = mbB + 32, mbE = mbA + 32;
    if (tid == 0) {
        for (int i = 0; i < 4; i++) { mbar_init(mbB + 8 * i, 1); mbar_init(mbA + 8 * i, 1); }
        mbar_init(mbE, 1);
        asm volatile("fence.mbarrier_init.release.cluster;" ::: "memory");
    }
    __syncthreads();
    if (warp < 4) {
        asm volatile("setmaxnreg.dec.sync.aligned.u32 96;");
        if (warp == 0) {
            if (lane == 0) {
                auto loadA = [&](int m) {
                    const uint32_t dst = sb + PP_A + (m % 3) * 32768;
                    mbar_expect_tx(mbA + 8 * m, 32768);
                    for (int kb = 0; kb < 4; kb++) {
                        if (z == 0) tma_2d(dst + kb * 8192, &tmWk, h * 256 + kb * 64, mh * 256 + m * 64, mbA + 8 * m);
                        else tma_2d(dst + kb * 8192, &tmWo, mh * 256 + m * 64, h * 256 + kb * 64, mbA + 8 * m);
                    }
                };
                loadA(0);
                for (int kb = 0; kb < 4; kb++) {
                    mbar_expect_tx(mbB + 8 * kb, 28672);
                    tma_2d(sb + PP_B + kb * 28672, z == 0 ? &tmWq : &tmWv, h * 256 + kb * 64, nh * 224, mbB + 8 * kb);
                    if (kb == 0) loadA(1);
                }
                loadA(2);
                if (nmt == 4) { mbar_wait(mbE, 0); loadA(3); }
            }
        } else {
            const int l28 = lane < 28 ? lane : 27;
            const uint4 w0 = __ldg(reinterpret_cast<const uint4*>(gate_w) + l28), w1 = __ldg(reinterpret_cast<const uint4*>(gate_w) + 28 + l28);
            uint4 x0[6], x1[6];
            #pragma unroll
            for (int q = 0; q < 6; q++) {
                const int k = warp - 1 + 3 * q;
                const int tok = blockIdx.x * 16 + (k < 16 ? k : 15);
                x0[q] = __ldg(reinterpret_cast<const uint4*>(Ax + (size_t)tok * D) + l28); x1[q] = __ldg(reinterpret_cast<const uint4*>(Ax + (size_t)tok * D) + 28 + l28);
            }
            #pragma unroll
            for (int q = 0; q < 6; q++) {
                const int k = warp - 1 + 3 * q;
                const uint32_t xs[8] = {x0[q].x, x0[q].y, x0[q].z, x0[q].w, x1[q].x, x1[q].y, x1[q].z, x1[q].w};
                const uint32_t ws[8] = {w0.x, w0.y, w0.z, w0.w, w1.x, w1.y, w1.z, w1.w};
                float s = 0.f;
                #pragma unroll
                for (int i = 0; i < 8; i++) s += bfr(bf_lo(xs[i]) * bf_lo(ws[i])) + bfr(bf_hi(xs[i]) * bf_hi(ws[i]));
                if (lane >= 28) s = 0.f;
                #pragma unroll
                for (int o = 16; o > 0; o >>= 1) s += __shfl_xor_sync(0xffffffffu, s, o);
                if (lane == 0 && k < 16) {
                    const int tok = blockIdx.x * 16 + k;
                    float sg = bfr(s);
                    float g = bfr(1.f / (1.f + __expf(-sg)));
                    g_gate[tok] = g; g_omg[tok] = bfr(1.f - g);
                }
            }
            const int at = tid - 32;
            for (int i = blockIdx.x * 96 + at; i < NSEG * CL * 80 * 3; i += PREP_ITEMS * 96) g_acc[i] = make_float4(0.f, 0.f, 0.f, 0.f);
            if (blockIdx.x == 0) {
                if (at < NSEG) { g_mem_ready[at] = 0; g_cnt_tx[at] = 0; g_cnt_v[at] = 0; }
                if (at < 16) { g_cnt_s5a[at] = 0; g_cnt_ga[at] = 0; }
                if (at < 4) g_q[at] = 0;
            }
            if (blockIdx.x == 1) for (int e = at; e < MEM * D / 2; e += 96) reinterpret_cast<uint32_t*>(g_mem)[e] = __ldg(reinterpret_cast<const uint32_t*>(mem0) + e);
        }
    } else {
        asm volatile("setmaxnreg.inc.sync.aligned.u32 200;");
        const int c = (warp >> 2) - 1, j = warp & 3;
        const float sc = z == 0 ? 0.0625f : 1.f;
        #pragma unroll 1
        for (int m = c; m < nmt; m += 2) {
            const uint32_t sA = sb + PP_A + (m % 3) * 32768;
            float acc[112];
            #pragma unroll
            for (int i = 0; i < 112; i++) acc[i] = 0.f;
            mbar_wait(mbA + 8 * m, 0);
            if (z == 0) {
                #pragma unroll 1
                for (int kb = 0; kb < 4; kb++) {
                    mbar_wait(mbB + 8 * kb, 0);
                    const uint64_t da = opaque64(desc_sw128(sA + kb * 8192)), db = opaque64(desc_sw128(sb + PP_B + kb * 28672));
                    wg_fence();
                    #pragma unroll
                    for (int ks = 0; ks < 4; ks++) wg_n224_ss(acc, da + 2 * ks, db + 2 * ks, 1);
                    wg_commit();
                }
            } else {
                #pragma unroll 1
                for (int kb = 0; kb < 4; kb++) {
                    mbar_wait(mbB + 8 * kb, 0);
                    const uint64_t da = opaque64(desc_sw128(sA + kb * 8192)), db = opaque64(desc_sw128(sb + PP_B + kb * 28672));
                    wg_fence();
                    #pragma unroll
                    for (int ks = 0; ks < 4; ks++) wg_n224_ss_ta(acc, da + 128 * ks, db + 2 * ks, 1);
                    wg_commit();
                }
            }
            wg_wait0();
            const int mt16 = mh * 16 + m * 4 + j;
            uint4* fo = (z == 0 ? g_AtF : g_UtF) + ((size_t)(h * 28 + mt16) * 28 + nh * 14) * 32 + lane;
            const uint32_t so = sA + (j * 16 + (lane >> 2)) * 448 + (lane & 3) * 4;
            const bool direct = (z == 1 && m == 0 && nmt == 4);
            if (z == 0 || direct) { if (c == 0) bar_sync(3, 128); else bar_sync(4, 128); }
            if (direct && j == 0 && lane == 0) mbar_arrive(mbE);
            bf16* nat = g_At + (size_t)h * D * D + (size_t)(mh * 256 + m * 64 + j * 16 + (lane >> 2)) * D + nh * 224 + 2 * (lane & 3);
            #pragma unroll
            for (int k = 0; k < 14; k++) {
                uint4 f;
                f.x = pack_bf16(acc[8 * k] * sc, acc[8 * k + 1] * sc); f.y = pack_bf16(acc[8 * k + 2] * sc, acc[8 * k + 3] * sc);
                f.z = pack_bf16(acc[8 * k + 4] * sc, acc[8 * k + 5] * sc); f.w = pack_bf16(acc[8 * k + 6] * sc, acc[8 * k + 7] * sc);
                fo[k * 32] = f;
                if (z == 0) {
                    if (direct) {
                        *reinterpret_cast<uint32_t*>(nat + 16 * k) = f.x; *reinterpret_cast<uint32_t*>(nat + 8 * D + 16 * k) = f.y;
                        *reinterpret_cast<uint32_t*>(nat + 16 * k + 8) = f.z; *reinterpret_cast<uint32_t*>(nat + 8 * D + 16 * k + 8) = f.w;
                    } else {
                        asm volatile("st.shared.u32 [%0], %1;" :: "r"(so + 32 * k), "r"(f.x) : "memory");
                        asm volatile("st.shared.u32 [%0], %1;" :: "r"(so + 8 * 448 + 32 * k), "r"(f.y) : "memory");
                        asm volatile("st.shared.u32 [%0], %1;" :: "r"(so + 32 * k + 16), "r"(f.z) : "memory");
                        asm volatile("st.shared.u32 [%0], %1;" :: "r"(so + 8 * 448 + 32 * k + 16), "r"(f.w) : "memory");
                    }
                }
            }
            if (z == 0 && !direct) {
                asm volatile("fence.proxy.async.shared::cta;" ::: "memory");
                if (c == 0) bar_sync(3, 128); else bar_sync(4, 128);
                if (j == 0 && lane == 0) {
                    asm volatile("cp.async.bulk.tensor.2d.global.shared::cta.bulk_group [%0, {%2, %3}], [%1];"
                        :: "l"(&tmAtS), "r"(sA), "r"(nh * 224), "r"(h * 448 + mh * 256 + m * 64) : "memory");
                    asm volatile("cp.async.bulk.commit_group;" ::: "memory");
                    if (m == 0 && nmt == 4) { asm volatile("cp.async.bulk.wait_group.read 0;" ::: "memory"); mbar_arrive(mbE); }
                }
            }
        }
        if (z == 0 && j == 0 && lane == 0) asm volatile("cp.async.bulk.wait_group 0;" ::: "memory");
    }
}
constexpr int XT_BYTES = 224 * 128;
constexpr uint32_t O_XT = 0;
constexpr uint32_t O_MEMF = 3 * XT_BYTES;
constexpr uint32_t O_SREDX = O_MEMF + 2 * 7168;
constexpr uint32_t O_SREDM = O_SREDX + 4 * 1280;
constexpr uint32_t O_SCX = O_SREDM + 4 * 256;
constexpr uint32_t O_SCM = O_SCX + 2 * CL * 512;
constexpr uint32_t O_PX4 = O_SCM + 2 * CL * 256;
constexpr uint32_t O_PM4 = O_PX4 + 4 * 2048;
constexpr uint32_t O_E = O_PM4 + 4 * 512;
constexpr uint32_t O_EST = O_E + 512;
constexpr uint32_t O_MB = O_EST + 256;
constexpr uint32_t CHAIN_SMEM = O_MB + 128;
constexpr int CHAIN_THREADS = 256;
#define TS(idx)
#define DBGCTA 7

__device__ __forceinline__ bool pk_ok(const float4& a, const float4& b, const float4& c) { return a.w == 16.f && b.w == 16.f && c.w == 16.f; }
__device__ __forceinline__ uint4 pk_pack(const float4& p0, const float4& p1, const float4& p2) {
    return make_uint4(pack_bf16(p0.x, p0.y), pack_bf16(p0.z, p2.x), pack_bf16(p1.x, p1.y), pack_bf16(p1.z, p2.y));
}
__device__ __forceinline__ uint4 poll_chunk(const float4* src, bool act) {
    float4 q0, q1, q2; int it = 0;
    q0.x = q0.y = q0.z = q1.x = q1.y = q1.z = q2.x = q2.y = 0.f;
    if (act) {
        do { q0 = ld_relaxed_f4(src); q1 = ld_relaxed_f4(src + 80); q2 = ld_relaxed_f4(src + 160); } while (!pk_ok(q0, q1, q2) && ++it < 100000);
        if (it >= 100000) atomicAdd(&g_err, 1);
    }
    return pk_pack(q0, q1, q2);
}

__device__ __forceinline__ void chain_final(uint32_t sb, int s, int lane, float* o0, float* o1, float mxl, float lx, uint32_t VM0, uint32_t VM1, float4* dst)
{
    const int p = s & 1;
    mbar_wait(sb + O_MB + 56 + 8 * p, (s >> 1) & 1);
    float s0, s1;
    {
        const uint32_t a = sb + O_SCM + p * (CL * 256) + lane * 8;
        float2 v0 = lf64(a), v1 = lf64(a + 256), v2 = lf64(a + 512), v3 = lf64(a + 768), v4 = lf64(a + 1024), v5 = lf64(a + 1280);
        s0 = (((v0.x + v1.x) + (v2.x + v3.x)) + (v4.x + v5.x)) * LOG2E; s1 = (((v0.y + v1.y) + (v2.y + v3.y)) + (v4.y + v5.y)) * LOG2E;
    }
    float mm = fmaxf(s0, s1);
    mm = fmaxf(mm, __shfl_xor_sync(0xffffffffu, mm, 1));
    mm = fmaxf(fmaxf(mm, mxl), __shfl_xor_sync(0xffffffffu, mm, 2));
    const float alpha = ex2(mxl - mm);
    uint32_t EM = pack_bf16(ex2(s0 - mm), ex2(s1 - mm));
    float lm = bf_lo(EM) + bf_hi(EM);
    o0[0] *= alpha; o0[1] *= alpha; o1[0] *= alpha; o1[1] *= alpha;
    mma8_nv(o0, EM, 0, VM0);
    mma8_nv(o1, EM, 0, VM1);
    lm += __shfl_xor_sync(0xffffffffu, lm, 1);
    lm += __shfl_xor_sync(0xffffffffu, lm, 2);
    const float inv = __fdividef(1.f, fmaf(lx, alpha, lm));
    float r0 = o0[0] * inv, r1 = o0[1] * inv, r2 = o1[0] * inv, r3 = o1[1] * inv;
    float nb = __shfl_down_sync(0xffffffffu, r3, 1);
    red_f4(dst + (lane & 1) * 80, r0, r1, r2, 1.f);
    if (!(lane & 1)) red_f4(dst + 160, r3, nb, 0.f, 1.f);
}

struct Confirm { uint2 v[5], m[2], w[5]; };
__device__ __forceinline__ uint2 ld_back(const uint2* p) {
    uint2 v; asm volatile("ld.relaxed.gpu.global.v2.u32 {%0,%1}, [%2];" : "=r"(v.x), "=r"(v.y) : "l"(p) : "memory"); return v;
}
__device__ __forceinline__ void confirm_issue(Confirm& c, const uint2* vf, const uint2* m0, const uint2* vf4) {
    #pragma unroll
    for (int i = 0; i < 5; i++) c.v[i] = ld_back(vf + 32 * i);
    c.m[0] = c.m[1] = make_uint2(0, 0);
    if (m0) { c.m[0] = ld_back(m0); c.m[1] = ld_back(m0 + 2); }
    #pragma unroll
    for (int i = 0; i < 5; i++) c.w[i] = make_uint2(0, 0);
    if (vf4) {
        #pragma unroll
        for (int i = 0; i < 5; i++) c.w[i] = ld_back(vf4 + 32 * i);
    }
}
__device__ __forceinline__ void confirm_finish(const Confirm& c, int lane, int* cnt, int* cntm) {
    uint32_t x = c.m[0].x | c.m[1].x;
    #pragma unroll
    for (int i = 0; i < 5; i++) x |= c.v[i].x | c.w[i].x;
    asm volatile("{\n.reg .pred p;\nsetp.eq.u32 p, %0, 0x7fc1fc3a;\n@p st.global.u32 [%1], %0;\n}" :: "r"(x), "l"(&g_sink) : "memory");
    __syncwarp();
    if (lane == 0) {
        asm volatile("red.relaxed.gpu.global.add.s32 [%0], 1;" :: "l"(cnt) : "memory");
        if (cntm) asm volatile("red.relaxed.gpu.global.add.s32 [%0], 1;" :: "l"(cntm) : "memory");
    }
}

__global__ void __launch_bounds__(CHAIN_THREADS, 1)
chain_kernel(const __grid_constant__ CUtensorMap tmX, const bf16* __restrict__ mem0, int backoff)
{
    extern __shared__ __align__(1024) uint8_t smem_raw[];
    uint32_t r; asm volatile("mov.u32 %0, %%cluster_ctarank;" : "=r"(r));
    const int h = blockIdx.x / CL;
    int tid; asm volatile("mov.u32 %0, %%tid.x;" : "=r"(tid));
    const int warp = __shfl_sync(0xffffffffu, tid >> 5, 0);
    int lane; asm volatile("mov.u32 %0, %%laneid;" : "=r"(lane));
    const int g = lane >> 2, t = lane & 3;
    const int off_r = r < 4 ? 80 * r : 320 + 64 * (r - 4);
    const bool wide = r < 4;
    const int nks = wide ? 5 : 4;
    const int nchunk = nks * 16;
    const int ks0 = off_r >> 4;
    long long* dbgp = (blockIdx.x == DBGCTA && lane == 0) ? g_dbg + warp * 16 : nullptr;
    (void)dbgp;
    uint32_t sb; asm volatile("mov.u32 %0, %1;" : "=r"(sb) : "r"(smem_u32(smem_raw)));
    const uint32_t a_mbX = sb + O_MB, a_mbMem = sb + O_MB + 24, a_mbMx = sb + O_MB + 40, a_mbMm = sb + O_MB + 56;

    if (tid == 0) {
        for (int i = 0; i < 3; i++) mbar_init(a_mbX + 8 * i, 1);
        for (int i = 0; i < 2; i++) { mbar_init(a_mbMem + 8 * i, 1 + ((nchunk + 31) >> 5)); mbar_init(a_mbMx + 8 * i, 5); mbar_init(a_mbMm + 8 * i, 2); }
        asm volatile("fence.mbarrier_init.release.cluster;" ::: "memory");
    }
    for (int e = tid; e < 28 * 32; e += CHAIN_THREADS) {
        int ks = e >> 5, l = e & 31, gg = l >> 2, tt = l & 3;
        const uint32_t* mp = reinterpret_cast<const uint32_t*>(mem0 + gg * D + ks * 16 + 2 * tt);
        *reinterpret_cast<uint2*>(smem_raw + O_MEMF + e * 8) = make_uint2(mp[0], mp[4]);
    }
    __syncthreads();
    auto load_x = [&](int s, int b) {
        mbar_expect_tx(a_mbX + 8 * b, XT_BYTES);
        asm volatile("cp.async.bulk.tensor.3d.shared::cluster.global.mbarrier::complete_tx::bytes.multicast::cluster [%0], [%1, {%3, %4, %5}], [%2], %6;"
            :: "r"(sb + O_XT + b * XT_BYTES + r * 4096), "l"(&tmX), "r"(a_mbX + 8 * b), "r"(0), "r"(s * 32), "r"((int)r), "h"((uint16_t)0x3f) : "memory");
        if (r == 0)
            asm volatile("cp.async.bulk.tensor.3d.shared::cluster.global.mbarrier::complete_tx::bytes.multicast::cluster [%0], [%1, {%3, %4, %5}], [%2], %6;"
                :: "r"(sb + O_XT + b * XT_BYTES + 6 * 4096), "l"(&tmX), "r"(a_mbX + 8 * b), "r"(0), "r"(s * 32), "r"(6), "h"((uint16_t)0x3f) : "memory");
    };
    asm volatile("barrier.cluster.arrive.release;\nbarrier.cluster.wait.acquire;" ::: "memory");
    if (tid == 0) { load_x(0, 0); load_x(1, 1); }
    asm volatile("griddepcontrol.wait;" ::: "memory");
    asm volatile("griddepcontrol.launch_dependents;" ::: "memory");

    const int lm = lane >> 3, lr = lane & 7;
    uint32_t peer[CL - 1];
    #pragma unroll
    for (int k = 0; k < CL - 1; k++) { uint32_t dst = r + 1 + k; if (dst >= CL) dst -= CL; peer[k] = mapa(sb, dst); }

    if (warp < 4) {
        const int w = warp;
        uint32_t A[7][5][4];
        {
            const uint4* af = g_AtF + ((size_t)(h * 28 + 7 * w) * 28 + ks0) * 32 + lane;
            #pragma unroll
            for (int i = 0; i < 7; i++)
                #pragma unroll
                for (int ks = 0; ks < 5; ks++) {
                    uint4 f = make_uint4(0, 0, 0, 0);
                    if (ks < nks) f = __ldcg(af + (i * 28 + ks) * 32);
                    A[i][ks][0] = f.x; A[i][ks][1] = f.y; A[i][ks][2] = f.z; A[i][ks][3] = f.w;
                }
        }
        const int atok = lr + 8 * (lm & 1);
        const uint32_t xrow = (uint32_t)(atok * 128), xsw = (uint32_t)(((atok & 7) ^ (lm >> 1)) << 4);
        const uint32_t a_sredx_w = sb + O_SREDX + w * 1280 + ((2 * t) * 20 + (g >> 1) * 4 + (g & 1)) * 4;
        const uint32_t a_sredm_w = sb + O_SREDM + w * 256 + ((2 * t) * 8 + g) * 4;
        const int L = 8 * w + (lane & 7);
        const uint32_t a_redx_r = sb + O_SREDX + ((L >> 2) * 20 + (L & 3) * 4) * 4;
        const float4* accp = g_acc + (size_t)(CL + r) * 240 + tid;
        const int mtg4 = ks0 + 4;
        int xb = 0; uint32_t xph = 0;
        for (int s = 0; s < NSEG; s++) {
            const int p = s & 1;
            const bool last = s == NSEG - 1;
            const uint32_t memp = sb + O_MEMF + p * 7168;
            if (!last && tid == 0) {
                mbar_expect_tx(a_mbMx + 8 * p, (CL - 1) * 512); mbar_expect_tx(a_mbMm + 8 * p, (CL - 1) * 256);
                mbar_expect_tx(a_mbMem + 8 * (p ^ 1), 7168 - nchunk * 16);
            }
            uint32_t F[7][2][4];
            const uint32_t xbase = sb + O_XT + xb * XT_BYTES + xrow;
            if (!last) {
                mbar_wait(a_mbX + 8 * xb, xph);
                #pragma unroll
                for (int i = 0; i < 4; i++) {
                    const int kk = 7 * w + i;
                    const uint32_t xa = xbase + (kk >> 2) * 4096 + (xsw ^ ((kk & 3) << 5));
                    ldsm4(F[i][0], xa); ldsm4(F[i][1], xa + 2048);
                }
            }
            TS(0);
            uint32_t VX4[4][2];
            if (w == 3) {
                if (wide) {
                    bar_sync(5, 128 + 32);
                    #pragma unroll
                    for (int b = 0; b < 4; b++) {
                        const uint32_t a = sb + O_PX4 + b * 512 + lane * 16;
                        float4 x0 = lf128(a), x1 = lf128(a + 2048), x2 = lf128(a + 4096), x3 = lf128(a + 6144);
                        VX4[b][0] = pack_bf16((x0.x + x1.x) + (x2.x + x3.x), (x0.y + x1.y) + (x2.y + x3.y));
                        VX4[b][1] = pack_bf16((x0.z + x1.z) + (x2.z + x3.z), (x0.w + x1.w) + (x2.w + x3.w));
                    }
                    uint2* vf = g_vfrag + ((size_t)(s * 28 + mtg4) * NH + h) * 5 * 32 + lane;
                    #pragma unroll
                    for (int b = 0; b < 4; b++) vf[(b + 1) * 32] = make_uint2(VX4[b][0], VX4[b][1]);
                }
            }
            if (s > 0) {
                if (w < 3) {
                    bar_sync(4, 224);
                    { long long t0 = clock64(); while (clock64() - t0 < backoff) {} }
                    const bool act = tid < nchunk;
                    uint4 cc = poll_chunk(accp, act);
                    if (act) {
                        const uint32_t o = O_MEMF + p * 7168 + ks0 * 256 + tid * 16;
                        ss128(sb + o, cc);
                        #pragma unroll
                        for (int k = 0; k < CL - 1; k++) st_async_v4(peer[k] + o, cc, peer[k] + O_MB + 24 + 8 * p);
                    }
                    accp += CL * 80 * 3;
                    __syncwarp();
                    if (w * 32 < nchunk && lane == 0) mbar_arrive(a_mbMem + 8 * p);
                    TS(10);
                }
                bar_sync(1, 128);
            }
            TS(1);
            if (!last) {
                float T[7][4];
                uint2 bm[5];
                #pragma unroll
                for (int ks = 0; ks < 5; ks++) bm[ks] = ks < nks ? ls64(memp + (ks0 + ks) * 256 + lane * 8) : make_uint2(0, 0);
                #pragma unroll
                for (int i = 0; i < 7; i++) T[i][0] = T[i][1] = T[i][2] = T[i][3] = 0.f;
                #pragma unroll
                for (int ks = 0; ks < 5; ks++)
                    #pragma unroll
                    for (int i = 0; i < 7; i++) mma_nv(T[i], A[i][ks][0], A[i][ks][1], A[i][ks][2], A[i][ks][3], bm[ks].x, bm[ks].y);
                #pragma unroll
                for (int i = 4; i < 7; i++) {
                    const int kk = 7 * w + i;
                    const uint32_t xa = xbase + (kk >> 2) * 4096 + (xsw ^ ((kk & 3) << 5));
                    ldsm4(F[i][0], xa); ldsm4(F[i][1], xa + 2048);
                }
                uint32_t tb0[7], tb1[7];
                #pragma unroll
                for (int i = 0; i < 7; i++) { tb0[i] = movm_nv(pack_bf16(T[i][0], T[i][1])); tb1[i] = movm_nv(pack_bf16(T[i][2], T[i][3])); }
                float sx[4][4];
                #pragma unroll
                for (int b = 0; b < 4; b++) sx[b][0] = sx[b][1] = sx[b][2] = sx[b][3] = 0.f;
                #pragma unroll
                for (int i = 0; i < 7; i++) {
                    mma_nv(sx[(i & 1) * 2 + 0], F[i][0][0], F[i][0][1], F[i][0][2], F[i][0][3], tb0[i], tb1[i]);
                    mma_nv(sx[(i & 1) * 2 + 1], F[i][1][0], F[i][1][1], F[i][1][2], F[i][1][3], tb0[i], tb1[i]);
                }
                #pragma unroll
                for (int i = 0; i < 2; i++) {
                    sf32(a_sredx_w + i * 640, sx[i][0] + sx[2 + i][0]); sf32(a_sredx_w + i * 640 + 80, sx[i][1] + sx[2 + i][1]);
                    sf32(a_sredx_w + i * 640 + 8, sx[i][2] + sx[2 + i][2]); sf32(a_sredx_w + i * 640 + 88, sx[i][3] + sx[2 + i][3]);
                }
                TS(2);
                bar_arrive(9, 256);
                bar_sync(2, 128);
                TS(3);
                if (lane < 8) {
                    float4 u0[4], u1[4];
                    #pragma unroll
                    for (int ww = 0; ww < 4; ww++) { u0[ww] = lf128(a_redx_r + ww * 1280); u1[ww] = lf128(a_redx_r + ww * 1280 + 640); }
                    float a[8];
                    a[0] = (u0[0].x + u0[1].x) + (u0[2].x + u0[3].x); a[1] = (u0[0].y + u0[1].y) + (u0[2].y + u0[3].y);
                    a[2] = (u0[0].z + u0[1].z) + (u0[2].z + u0[3].z); a[3] = (u0[0].w + u0[1].w) + (u0[2].w + u0[3].w);
                    a[4] = (u1[0].x + u1[1].x) + (u1[2].x + u1[3].x); a[5] = (u1[0].y + u1[1].y) + (u1[2].y + u1[3].y);
                    a[6] = (u1[0].z + u1[1].z) + (u1[2].z + u1[3].z); a[7] = (u1[0].w + u1[1].w) + (u1[2].w + u1[3].w);
                    #pragma unroll
                    for (int j = 0; j < 8; j++) a[j] = fminf(fmaxf(a[j], -16000.f), 16000.f);
                    uint4 c = make_uint4(pack_f16_sat(a[0], a[1]), pack_f16_sat(a[2], a[3]), pack_f16_sat(a[4], a[5]), pack_f16_sat(a[6], a[7]));
                    const uint32_t o = O_SCX + (p * CL + r) * 512 + L * 16;
                    #pragma unroll
                    for (int k = 0; k < CL - 1; k++) st_async_v4(peer[k] + o, c, peer[k] + O_MB + 40 + 8 * p);
                    ss128(sb + o, c);
                }
                __syncwarp();
                if (lane == 0) mbar_arrive(a_mbMx + 8 * p);
                TS(4);
                if (s > 0) mbar_wait(a_mbMem + 8 * p, ((s - 1) >> 1) & 1);
                TS(5);
                float sm0[4] = {0,0,0,0}, sm1[4] = {0,0,0,0};
                {
                    uint2 b[7];
                    #pragma unroll
                    for (int i = 0; i < 7; i++) b[i] = ls64(memp + (7 * w + i) * 256 + lane * 8);
                    #pragma unroll
                    for (int i = 0; i < 7; i++) mma_nv((i & 1) ? sm1 : sm0, b[i].x, b[i].x, b[i].y, b[i].y, tb0[i], tb1[i]);
                }
                sf32(a_sredm_w, sm0[0] + sm1[0]); sf32(a_sredm_w + 32, sm0[1] + sm1[1]);
                TS(6);
                if (w != 2) bar_arrive(3, 128); else bar_sync(3, 128);
                if (w == 2) {
                    if (lane < 16) {
                        const uint32_t ar = sb + O_SREDM + lane * 16;
                        float4 u0 = lf128(ar), u1 = lf128(ar + 256), u2 = lf128(ar + 512), u3 = lf128(ar + 768);
                        uint4 c = make_uint4(__float_as_uint((u0.x + u1.x) + (u2.x + u3.x)), __float_as_uint((u0.y + u1.y) + (u2.y + u3.y)),
                                             __float_as_uint((u0.z + u1.z) + (u2.z + u3.z)), __float_as_uint((u0.w + u1.w) + (u2.w + u3.w)));
                        const uint32_t o = O_SCM + (p * CL + r) * 256 + lane * 16;
                        #pragma unroll
                        for (int k = 0; k < CL - 1; k++) st_async_v4(peer[k] + o, c, peer[k] + O_MB + 56 + 8 * p);
                        ss128(sb + o, c);
                    }
                    __syncwarp();
                    if (lane == 0) mbar_arrive(a_mbMm + 8 * p);
                }
                if (tid == 0 && s + 2 < NSEG) { int b2 = xb + 2; if (b2 >= 3) b2 -= 3; load_x(s + 2, b2); }
            }
            if (wide && w == 3) {
                bar_sync(8, 128 + 32);
                const uint32_t am = sb + O_PM4 + lane * 16;
                float4 m0 = lf128(am), m1 = lf128(am + 512), m2 = lf128(am + 1024), m3 = lf128(am + 1536);
                uint32_t VM0 = pack_bf16((m0.x + m1.x) + (m2.x + m3.x), (m0.y + m1.y) + (m2.y + m3.y));
                uint32_t VM1 = pack_bf16((m0.z + m1.z) + (m2.z + m3.z), (m0.w + m1.w) + (m2.w + m3.w));
                g_vfrag[((size_t)(s * 28 + mtg4) * NH + h) * 5 * 32 + lane] = make_uint2(VM0, VM1);
                bar_arrive(6, 128 + 32);
                if (!last) {
                    bar_sync(7, 64);
                    uint4 E = ls128(sb + O_E + lane * 16);
                    float mxl; asm volatile("ld.shared.f32 %0, [%1];" : "=f"(mxl) : "r"(sb + O_EST + lane * 4));
                    float o0[4] = {0,0,0,0}, o1[4] = {0,0,0,0};
                    mma_nv(o0, E.x, 0, E.y, 0, VX4[0][0], VX4[1][0]);
                    mma_nv(o1, E.x, 0, E.y, 0, VX4[0][1], VX4[1][1]);
                    mma_nv(o0, E.z, 0, E.w, 0, VX4[2][0], VX4[3][0]);
                    mma_nv(o1, E.z, 0, E.w, 0, VX4[2][1], VX4[3][1]);
                    float lx = ((bf_lo(E.x) + bf_hi(E.x)) + (bf_lo(E.y) + bf_hi(E.y))) + ((bf_lo(E.z) + bf_hi(E.z)) + (bf_lo(E.w) + bf_hi(E.w)));
                    lx += __shfl_xor_sync(0xffffffffu, lx, 1);
                    lx += __shfl_xor_sync(0xffffffffu, lx, 2);
                    chain_final(sb, s, lane, o0, o1, mxl, lx, VM0, VM1, g_acc + (size_t)((s + 1) * CL + r) * 240 + 64 + (lane >> 1));
                }
            }
            TS(9);
            if (++xb == 3) { xb = 0; xph ^= 1; }
        }
    } else {
        const int u = warp - 4;
        uint32_t U[28][4], U4[7][4];
        {
            const uint4* uf = g_UtF + ((size_t)(h * 28 + ks0 + u) * 28) * 32 + lane;
            #pragma unroll
            for (int ks = 0; ks < 28; ks++) { uint4 f = __ldcg(uf + ks * 32); U[ks][0] = f.x; U[ks][1] = f.y; U[ks][2] = f.z; U[ks][3] = f.w; }
            const uint4* uf4 = g_UtF + ((size_t)(h * 28 + ks0 + 4) * 28 + 7 * u) * 32 + lane;
            #pragma unroll
            for (int k = 0; k < 7; k++) {
                uint4 f = make_uint4(0, 0, 0, 0);
                if (wide) f = __ldcg(uf4 + k * 32);
                U4[k][0] = f.x; U4[k][1] = f.y; U4[k][2] = f.z; U4[k][3] = f.w;
            }
        }
        const int xtok = 8 * (lm >> 1) + lr;
        const uint32_t xrow = (uint32_t)(xtok * 128), xy = (uint32_t)(((xtok & 7) ^ (lm & 1)) << 4);
        const int nsend = nchunk >> 2;
        const int ch = u * nsend + lane;
        const int mtg = ks0 + u;
        float4* accp = g_acc + (size_t)(CL + r) * 240 + u * 16 + (lane >> 1);
        uint2* vf = g_vfrag + ((size_t)mtg * NH + h) * 5 * 32 + lane;
        auto mem_words = [&](int sg) -> const uint2* {
            if (!(h == 0 && sg > 0 && lane < nsend)) return nullptr;
            int ks = ch >> 4, m = ch & 15, gg = m >> 1, uu = m & 1;
            return reinterpret_cast<const uint2*>(g_mem + ((size_t)sg * MEM + gg) * D + off_r + 16 * ks + 4 * uu);
        };
        int xb = 0; uint32_t xph = 0;
        for (int s = 0; s < NSEG; s++) {
            const int p = s & 1;
            const uint32_t memp = sb + O_MEMF + p * 7168;
            float c[4][4];
            uint32_t VX[4][2];
            Confirm cf;
            TS(0);
            mbar_wait(a_mbX + 8 * xb, xph);
            {
                const uint32_t xt = sb + O_XT + xb * XT_BYTES;
                const uint64_t d0 = desc_sw128(xt);
                #pragma unroll
                for (int b = 0; b < 4; b++) c[b][0] = c[b][1] = c[b][2] = c[b][3] = 0.f;
                if (wide) {
                    float c4[4][4];
                    #pragma unroll
                    for (int b = 0; b < 4; b++) c4[b][0] = c4[b][1] = c4[b][2] = c4[b][3] = 0.f;
                    uint32_t f0[7][4], f1[7][4];
                    #pragma unroll
                    for (int k = 0; k < 7; k++) {
                        const int kk = 7 * u + k;
                        const uint32_t xa = xt + xrow + (kk >> 2) * 4096 + (xy ^ ((kk & 3) << 5));
                        ldsm4(f0[k], xa); ldsm4(f1[k], xa + 2048);
                    }
                    #pragma unroll
                    for (int k = 0; k < 7; k++) {
                        mma_nv(c4[0], U4[k][0], U4[k][1], U4[k][2], U4[k][3], f0[k][0], f0[k][1]);
                        mma_nv(c4[1], U4[k][0], U4[k][1], U4[k][2], U4[k][3], f0[k][2], f0[k][3]);
                        mma_nv(c4[2], U4[k][0], U4[k][1], U4[k][2], U4[k][3], f1[k][0], f1[k][1]);
                        mma_nv(c4[3], U4[k][0], U4[k][1], U4[k][2], U4[k][3], f1[k][2], f1[k][3]);
                    }
                    if (s > 0) bar_sync(6, 128 + 32);
                    #pragma unroll
                    for (int b = 0; b < 4; b++) sf128(sb + O_PX4 + u * 2048 + b * 512 + lane * 16, c4[b][0], c4[b][1], c4[b][2], c4[b][3]);
                    bar_arrive(5, 128 + 32);
                }
                if (s > 0) confirm_issue(cf, vf - (size_t)28 * NH * 5 * 32, mem_words(s - 1), (wide && u == 0) ? vf - (size_t)28 * NH * 5 * 32 + (size_t)4 * NH * 5 * 32 : nullptr);
                wg_fence();
                #pragma unroll
                for (int ks = 0; ks < 28; ks++) wg_n32_rs(&c[0][0], U[ks][0], U[ks][1], U[ks][2], U[ks][3], d0 + (uint64_t)(((ks >> 2) * 4096 + (ks & 3) * 32) >> 4), 1);
                wg_commit();
                wg_wait0();
            }
            #pragma unroll
            for (int b = 0; b < 4; b++) { VX[b][0] = pack_bf16(c[b][0], c[b][1]); VX[b][1] = pack_bf16(c[b][2], c[b][3]); }
            #pragma unroll
            for (int b = 0; b < 4; b++) vf[(b + 1) * 32] = make_uint2(VX[b][0], VX[b][1]);
            if (s > 0) confirm_finish(cf, lane, &g_cnt_v[s - 1], h == 0 ? &g_mem_ready[s - 1] : nullptr);
            TS(1);
            if (s > 0) mbar_wait(a_mbMem + 8 * p, ((s - 1) >> 1) & 1);
            TS(5);
            uint32_t VM0, VM1;
            {
                uint2 bb[28], b4[7];
                #pragma unroll
                for (int k = 0; k < 7; k++) b4[k] = wide ? ls64(memp + (7 * u + k) * 256 + lane * 8) : make_uint2(0, 0);
                #pragma unroll
                for (int ks = 0; ks < 28; ks++) bb[ks] = ls64(memp + ks * 256 + lane * 8);
                if (s < NSEG - 1) bar_sync(9, 256);
                float d[7][4];
                #pragma unroll
                for (int b = 0; b < 7; b++) d[b][0] = d[b][1] = d[b][2] = d[b][3] = 0.f;
                if (wide) {
                    float e[4][4];
                    #pragma unroll
                    for (int b = 0; b < 4; b++) e[b][0] = e[b][1] = e[b][2] = e[b][3] = 0.f;
                    #pragma unroll
                    for (int k = 0; k < 7; k++) mma_nv(e[k & 3], U4[k][0], U4[k][1], U4[k][2], U4[k][3], b4[k].x, b4[k].y);
                    #pragma unroll
                    for (int ks = 0; ks < 7; ks++) mma_nv(d[ks], U[ks][0], U[ks][1], U[ks][2], U[ks][3], bb[ks].x, bb[ks].y);
                    sf128(sb + O_PM4 + u * 512 + lane * 16, (e[0][0] + e[1][0]) + (e[2][0] + e[3][0]), (e[0][1] + e[1][1]) + (e[2][1] + e[3][1]),
                          (e[0][2] + e[1][2]) + (e[2][2] + e[3][2]), (e[0][3] + e[1][3]) + (e[2][3] + e[3][3]));
                    bar_arrive(8, 128 + 32);
                } else {
                    #pragma unroll
                    for (int ks = 0; ks < 7; ks++) mma_nv(d[ks], U[ks][0], U[ks][1], U[ks][2], U[ks][3], bb[ks].x, bb[ks].y);
                }
                #pragma unroll
                for (int ks = 7; ks < 28; ks++) mma_nv(d[ks % 7], U[ks][0], U[ks][1], U[ks][2], U[ks][3], bb[ks].x, bb[ks].y);
                float v[4];
                #pragma unroll
                for (int q = 0; q < 4; q++) v[q] = ((d[0][q] + d[1][q]) + (d[2][q] + d[3][q])) + ((d[4][q] + d[5][q]) + d[6][q]);
                VM0 = pack_bf16(v[0], v[1]); VM1 = pack_bf16(v[2], v[3]);
            }
            TS(6);
            if (s < NSEG - 1) {
                mbar_wait(a_mbMx + 8 * p, (s >> 1) & 1);
                TS(7);
                float sx8[8];
                {
                    const uint32_t a = sb + O_SCX + p * (CL * 512) + lane * 16;
                    uint4 v[6];
                    #pragma unroll
                    for (int k = 0; k < 6; k++) v[k] = ls128(a + k * 512);
                    #pragma unroll
                    for (int j = 0; j < 4; j++) {
                        __half2 h0 = __hadd2(*reinterpret_cast<const __half2*>(&(&v[0].x)[j]), *reinterpret_cast<const __half2*>(&(&v[1].x)[j]));
                        __half2 h1 = __hadd2(*reinterpret_cast<const __half2*>(&(&v[2].x)[j]), *reinterpret_cast<const __half2*>(&(&v[3].x)[j]));
                        __half2 h2 = __hadd2(*reinterpret_cast<const __half2*>(&(&v[4].x)[j]), *reinterpret_cast<const __half2*>(&(&v[5].x)[j]));
                        float2 f0 = __half22float2(h0), f1 = __half22float2(h1), f2 = __half22float2(h2);
                        sx8[2 * j] = (f0.x + f1.x + f2.x) * LOG2E; sx8[2 * j + 1] = (f0.y + f1.y + f2.y) * LOG2E;
                    }
                }
                float mx = fmaxf(fmaxf(fmaxf(sx8[0], sx8[1]), fmaxf(sx8[2], sx8[3])), fmaxf(fmaxf(sx8[4], sx8[5]), fmaxf(sx8[6], sx8[7])));
                mx = fmaxf(mx, __shfl_xor_sync(0xffffffffu, mx, 1));
                mx = fmaxf(mx, __shfl_xor_sync(0xffffffffu, mx, 2));
                uint32_t E[4];
                float lx = 0.f;
                #pragma unroll
                for (int j = 0; j < 4; j++) {
                    E[j] = pack_bf16(ex2(sx8[2 * j] - mx), ex2(sx8[2 * j + 1] - mx));
                    lx += bf_lo(E[j]) + bf_hi(E[j]);
                }
                if (wide && u == 0) {
                    ss128(sb + O_E + lane * 16, make_uint4(E[0], E[1], E[2], E[3]));
                    sf32(sb + O_EST + lane * 4, mx);
                    bar_arrive(7, 64);
                }
                float o0[4] = {0,0,0,0}, o1[4] = {0,0,0,0};
                mma_nv(o0, E[0], 0, E[1], 0, VX[0][0], VX[1][0]);
                mma_nv(o1, E[0], 0, E[1], 0, VX[0][1], VX[1][1]);
                mma_nv(o0, E[2], 0, E[3], 0, VX[2][0], VX[3][0]);
                mma_nv(o1, E[2], 0, E[3], 0, VX[2][1], VX[3][1]);
                lx += __shfl_xor_sync(0xffffffffu, lx, 1);
                lx += __shfl_xor_sync(0xffffffffu, lx, 2);
                TS(8);
                chain_final(sb, s, lane, o0, o1, mx, lx, VM0, VM1, accp);
                TS(10);
            }
            vf[0] = make_uint2(VM0, VM1);
            if (h == 0 && s > 0 && lane < nsend) {
                uint4 cc = ls128(memp + ks0 * 256 + ch * 16);
                int ks = ch >> 4, m = ch & 15, gg = m >> 1, uu = m & 1;
                bf16* dst = g_mem + ((size_t)s * MEM + gg) * D + off_r + 16 * ks + 4 * uu;
                *reinterpret_cast<uint2*>(dst) = make_uint2(cc.x, cc.z);
                *reinterpret_cast<uint2*>(dst + 8) = make_uint2(cc.y, cc.w);
            }
            if (s < NSEG - 1) bar_arrive(4, 224);
            else {
                if (wide) bar_sync(6, 128 + 32);
                confirm_issue(cf, vf, mem_words(s), (wide && u == 0) ? vf + (size_t)4 * NH * 5 * 32 : nullptr);
                confirm_finish(cf, lane, &g_cnt_v[s], h == 0 ? &g_mem_ready[s] : nullptr);
            }
            accp += CL * 80 * 3;
            vf += (size_t)28 * NH * 5 * 32;
            if (++xb == 3) { xb = 0; xph ^= 1; }
        }
    }
    asm volatile("barrier.cluster.arrive.release;\nbarrier.cluster.wait.acquire;" ::: "memory");
}

constexpr int BULK_THREADS = 384;
constexpr uint32_t BK_R0 = 0;
constexpr uint32_t BK_R1 = 114688;
constexpr uint32_t BK_RM = BK_R1 + 3 * 28672;
constexpr uint32_t BK_MB = BK_RM + 28672;
constexpr uint32_t BULK_SMEM = BK_MB + 256;

#define WAIT_NS 100
#define ITEM_LIMIT N_ITEMS
constexpr int N_MEMSIG = 24, N_VSIG = 384;
struct cplx { float x, y; };
__device__ __forceinline__ cplx cmadd(cplx a, cplx b, cplx c) { cplx r; r.x = fmaf(a.x, b.x, fmaf(-a.y, b.y, c.x)); r.y = fmaf(a.x, b.y, fmaf(a.y, b.x, c.y)); return r; }
__device__ __forceinline__ cplx cpowk(float a, float b, float k) { float e = expf(a * k), s, c; sincosf(b * k, &s, &c); cplx r; r.x = e * c; r.y = e * s; return r; }

__device__ __forceinline__ void wait_count(const int* p, int target) {
    int it = 0;
    while (true) {
        int v; asm volatile("ld.acquire.gpu.global.s32 %0, [%1];" : "=r"(v) : "l"(p) : "memory");
        if (v >= target) break;
        __nanosleep(WAIT_NS);
        if (++it > 2000000) { atomicAdd(&g_err, 1); break; }
    }
}
__device__ __forceinline__ void signal_count(int* p) {
    __threadfence();
    asm volatile("red.release.gpu.global.add.s32 [%0], 1;" :: "l"(p) : "memory");
}
__device__ __forceinline__ void fence_async_global() { asm volatile("fence.proxy.async.global;" ::: "memory"); }

constexpr int N_ITEMS = 455;
__device__ const int g_order[455] = {0,256,512,768,1024,1280,1536,65552,65554,65556,65558,65560,65562,65564,65566,131072,131073,131328,131329,65808,65810,65812,65814,65816,65818,65820,65822,131584,131585,131840,131841,66064,66066,66068,66070,66072,66074,66076,66078,132096,132097,196608,196609,196610,196611,196864,196865,196866,196867,197120,197121,197122,197123,197376,197377,197378,197379,132352,132353,66320,66322,66324,66326,66328,66330,66332,66334,132608,132609,197632,197633,197634,197635,197888,197889,197890,197891,198144,198145,198146,198147,198400,198401,198402,198403,132864,132865,66576,66578,66580,66582,66584,66586,66588,66590,133120,133121,198656,198657,198658,198659,198912,198913,198914,198915,199168,199169,199170,199171,199424,199425,199426,199427,133376,133377,66832,66834,66836,66838,66840,66842,66844,66846,133632,133633,133888,133889,199680,199681,199682,199683,199936,199937,199938,199939,200192,200193,200194,200195,200448,200449,200450,200451,67088,67090,67092,67094,67096,67098,67100,67102,134144,134145,134400,134401,200704,200705,200706,200707,200960,200961,200962,200963,201216,201217,201218,201219,201472,201473,201474,201475,134656,134657,67344,67346,67348,67350,67352,67354,67356,67358,134912,134913,201728,201729,201730,201731,201984,201985,201986,201987,202240,202241,202242,202243,202496,202497,202498,202499,67600,67602,67604,67606,67608,67610,67612,67614,202752,202753,202754,202755,203008,203009,203010,203011,203264,203265,203266,203267,203520,203521,203522,203523,67856,67858,67860,67862,67864,67866,67868,67870,203776,203777,203778,203779,204032,204033,204034,204035,204288,204289,204290,204291,204544,204545,204546,204547,68112,68114,68116,68118,68120,68122,68124,68126,204800,204801,204802,204803,205056,205057,205058,205059,205312,205313,205314,205315,205568,205569,205570,205571,68368,68370,68372,68374,68376,68378,68380,68382,205824,205825,205826,205827,206080,206081,206082,206083,206336,206337,206338,206339,206592,206593,206594,206595,68608,68609,68610,68611,68612,68613,68614,68615,68616,68617,68618,68619,68620,68621,68622,68623,68864,68865,68866,68867,68868,68869,68870,68871,68872,68873,68874,68875,68876,68877,68878,68879,69376,69377,69378,69379,69380,69381,69382,69383,69384,69385,69386,69387,69388,69389,69390,69391,69120,69121,69122,69123,69124,69125,69126,69127,69128,69129,69130,69131,69132,69133,69134,69135,206848,206849,206850,206851,207104,207105,207106,207107,207360,207361,207362,207363,207616,207617,207618,207619,207872,207873,207874,207875,208128,208129,208130,208131,208384,208385,208386,208387,208640,208641,208642,208643,208896,208897,208898,208899,209152,209153,209154,209155,209408,209409,209410,209411,209664,209665,209666,209667,209920,209921,209922,209923,210176,210177,210178,210179,210432,210433,210434,210435,210688,210689,210690,210691,210944,210945,210946,210947,211200,211201,211202,211203,211456,211457,211458,211459,211712,211713,211714,211715,211968,211969,211970,211971,212224,212225,212226,212227,212480,212481,212482,212483,212736,212737,212738,212739};

__device__ __forceinline__ int pick_item() { int i = atomicAdd(&g_q[0], 1); return i < N_ITEMS ? g_order[i] : -1; }

struct BulkParams {
    CUtensorMap X128, Mem, At, Bre, Bim, H, Cre, Cim;
    const bf16 *Ax, *Lre, *Lim, *logdt, *Dskip;
    float* out;
};

__global__ void __launch_bounds__(BULK_THREADS, 1)
bulk_kernel(const __grid_constant__ BulkParams P)
{
    extern __shared__ __align__(1024) uint8_t smem_raw[];
    const int tid = threadIdx.x, warp = __shfl_sync(0xffffffffu, tid >> 5, 0), lane = tid & 31;
    const uint32_t sb = smem_u32(smem_raw);
    const uint32_t mbF = sb + BK_MB, mbE = mbF + 24, mbR = mbF + 48, mbM = mbF + 56, aItem = mbF + 64;
    if (tid == 0) {
        for (int i = 0; i < 3; i++) { mbar_init(mbF + 8 * i, 1); mbar_init(mbE + 8 * i, 8); }
        mbar_init(mbR, 1); mbar_init(mbM, 1);
        for (int i = 0; i < 7; i++) { mbar_init(mbF + 80 + 8 * i, 1); mbar_init(mbF + 136 + 8 * i, 8); mbar_init(mbF + 192 + 8 * i, 1); }
        asm volatile("fence.mbarrier_init.release.cluster;" ::: "memory");
    }
    __syncthreads();
    if (warp < 4) {
        asm volatile("setmaxnreg.dec.sync.aligned.u32 40;");
        uint32_t st = 0, ph = 1;
        while (true) {
            if (tid == 0) { int i = ITEM_LIMIT > 0 ? pick_item() : -1; asm volatile("st.shared.s32 [%0], %1;" :: "r"(aItem), "r"(i) : "memory"); }
            bar_sync(1, BULK_THREADS);
            int item; asm volatile("ld.shared.s32 %0, [%1];" : "=r"(item) : "r"(aItem) : "memory");
            bar_sync(2, BULK_THREADS);
            if (item < 0) break;
            const int type = item >> 16, a = (item >> 8) & 255, b = item & 255;
            if (type == 0 && (warp == 1 || warp == 2)) {
                for (int tile = 0; tile < 16; tile++) {
                    if (warp == 1) bar_sync(3, 160); else bar_sync(4, 160);
                    if (lane == 0) { fence_async_global(); signal_count(&g_cnt_s5a[tile]); }
                    __syncwarp();
                }
            }
            if (warp == 0) {
                if (type == 0) {
                    if (lane == 0) mbar_expect_tx(mbR, 2 * 57344);
                    __syncwarp();
                    for (int e = lane; e < 112; e += 32) {
                        const int part = e & 1, j = (e >> 1) & 3, kb = (e >> 3) % 7, c = e / 56;
                        tma_2d(sb + BK_R0 + c * 57344 + kb * 8192 + (16 * j + 8 * part) * 128, part ? &P.Bim : &P.Bre, kb * 64, a * 64 + c * 32 + 8 * j, mbR);
                    }
                    if (lane == 0) {
                        for (int tile = 0; tile < 16; tile++)
                            for (int kb = 0; kb < 7; kb++) {
                                mbar_wait(mbF + 136 + 8 * kb, (tile & 1) ^ 1);
                                mbar_expect_tx(mbF + 80 + 8 * kb, 16384);
                                tma_2d(sb + BK_R1 + kb * 16384, &P.X128, kb * 64, tile * 128, mbF + 80 + 8 * kb);
                            }
                    }
                } else if (type == 1) {
                    if (lane == 0) {
                        mbar_expect_tx(mbR, 7 * 16384);
                        for (int kb = 0; kb < 7; kb++) tma_2d(sb + BK_R0 + kb * 16384, &P.X128, kb * 64, a * 128, mbR);
                        const int h0 = b >= 16 ? b - 16 : b, nhd = b >= 16 ? 2 : 1;
                        for (int hh = 0; hh < nhd; hh++) {
                            for (int q = 0; q < 14; q++) {
                                mbar_wait(mbE + 8 * st, ph);
                                mbar_expect_tx(mbF + 8 * st, 28672);
                                tma_2d(sb + BK_R1 + st * 28672, &P.At, (q % 7) * 64, (h0 + hh) * 448 + (q / 7) * 224, mbF + 8 * st);
                                if (++st == 3) { st = 0; ph ^= 1; }
                            }
                            if (hh == 0) {
                                for (int sg = 0; sg < 4; sg++) if (4 * a + sg > 0) wait_count(&g_mem_ready[4 * a + sg], N_MEMSIG);
                                fence_async_global();
                                mbar_expect_tx(mbM, 28672);
                                for (int kb = 0; kb < 7; kb++) tma_2d(sb + BK_RM + kb * 4096, &P.Mem, kb * 64, a * 32, mbM);
                            }
                        }
                    }
                } else if (type == 2) {
                    if (lane == 0) {
                        wait_count(&g_cnt_s5a[a], 14);
                        fence_async_global();
                        for (int q = 0; q < 14; q++) {
                            const int part = q / 7, kb = q % 7;
                            mbar_wait(mbE + 8 * st, ph);
                            mbar_expect_tx(mbF + 8 * st, 16384 + 28672);
                            const uint32_t ab = sb + BK_R0 + kb * 16384;
                            tma_2d(ab, &P.H, a * 128, part * 448 + kb * 64, mbF + 8 * st);
                            tma_2d(ab + 8192, &P.H, a * 128 + 64, part * 448 + kb * 64, mbF + 8 * st);
                            tma_2d(sb + BK_R1 + st * 28672, part ? &P.Cim : &P.Cre, kb * 64, b * 224, mbF + 8 * st);
                            if (++st == 3) { st = 0; ph ^= 1; }
                        }
                    }
                } else {
                    if (lane == 0) {
                        wait_count(&g_cnt_v[a], N_VSIG);
                        fence_async_global();
                        for (int m = 0; m < 7; m++) {
                            mbar_expect_tx(mbF + 192 + 8 * m, 20480);
                            asm volatile("cp.async.bulk.shared::cta.global.mbarrier::complete_tx::bytes [%0], [%1], %2, [%3];"
                                :: "r"(sb + BK_R0 + 40960 + m * 20480), "l"(g_vfrag + (size_t)(a * 28 + b * 7 + m) * 80 * 32), "r"(20480), "r"(mbF + 192 + 8 * m) : "memory");
                        }
                        wait_count(&g_cnt_ga[a >> 2], 16);
                        wait_count(&g_cnt_tx[a], 32);
                        fence_async_global();
                        mbar_expect_tx(mbR, 40960);
                        asm volatile("cp.async.bulk.shared::cta.global.mbarrier::complete_tx::bytes [%0], [%1], %2, [%3];"
                            :: "r"(sb + BK_R0), "l"(g_pfrag + (size_t)a * 2 * 80 * 32), "r"(40960), "r"(mbR) : "memory");
                    }
                }
            }
        }
        asm volatile("griddepcontrol.wait;" ::: "memory");
    } else {
        asm volatile("setmaxnreg.inc.sync.aligned.u32 232;");
        uint32_t st = 0, ph = 0, rph = 0, mph = 0, fph = 0;
        const uint32_t sb0 = sb; const int warp0 = warp, lane0 = lane;
        while (true) {
            bar_sync(1, BULK_THREADS);
            int item; asm volatile("ld.shared.s32 %0, [%1];" : "=r"(item) : "r"(aItem) : "memory");
            bar_sync(2, BULK_THREADS);
            if (item < 0) break;
            uint32_t sb; int warp, lane;
            asm volatile("mov.u32 %0, %1;" : "=r"(sb) : "r"(sb0)); asm volatile("mov.u32 %0, %1;" : "=r"(warp) : "r"(warp0)); asm volatile("mov.u32 %0, %1;" : "=r"(lane) : "r"(lane0));
            const uint32_t mbF = sb + BK_MB, mbE = mbF + 24, mbR = mbF + 48, mbM = mbF + 56;
            const int c = (warp >> 2) - 1, j = warp & 3, g = lane >> 2, t = lane & 3, cw = warp - 4;
            const int type = item >> 16, a = (item >> 8) & 255, b = item & 255;
            if (type == 0) {
                const int ch = a * 64 + c * 32 + 8 * j + g;
                const float lre = __bfloat162float(P.Lre[ch]), lim = __bfloat162float(P.Lim[ch]);
                const float dt = bfr(expf(__bfloat162float(P.logdt[ch])));
                const float pa = dt * lre, pb = dt * lim;
                const cplx l1 = cpowk(pa, pb, 1.f), l2 = cpowk(pa, pb, 2.f), l4 = cpowk(pa, pb, 4.f), l8 = cpowk(pa, pb, 8.f);
                const cplx pw0 = cpowk(pa, pb, (float)(2 * t + 1)), pw1 = cpowk(pa, pb, (float)(2 * t + 2));
                cplx coef;
                { const float nx = l1.x - 1.f, ny = l1.y, den = lre * lre + lim * lim; coef.x = (nx * lre + ny * lim) / den; coef.y = (ny * lre - nx * lim) / den; }
                cplx carry; carry.x = 0.f; carry.y = 0.f;
                bf16* hre = g_hT + (size_t)ch * NTOK;
                bf16* him = g_hT + (size_t)(D + ch) * NTOK;
                mbar_wait(mbR, rph); rph ^= 1;
                #pragma unroll 1
                for (int tile = 0; tile < 16; tile++) {
                    float acc[64];
                    #pragma unroll
                    for (int i = 0; i < 64; i++) acc[i] = 0.f;
                    if (c == 1) bar_sync(5, 256); else if (tile > 0) bar_sync(6, 256);
                    #pragma unroll 1
                    for (int kb = 0; kb < 7; kb++) {
                        mbar_wait(mbF + 80 + 8 * kb, tile & 1);
                        const uint64_t da = opaque64(desc_sw128(sb + BK_R0 + c * 57344 + kb * 8192)), db = opaque64(desc_sw128(sb + BK_R1 + kb * 16384));
                        wg_fence();
                        #pragma unroll
                        for (int ks = 0; ks < 4; ks++) wg_n128_ss(acc, da + 2 * ks, db + 2 * ks, 1);
                        wg_commit();
                        wg_wait1();
                        if (kb > 0 && lane == 0) mbar_arrive(mbF + 136 + 8 * (kb - 1));
                    }
                    wg_wait0();
                    if (lane == 0) mbar_arrive(mbF + 136 + 8 * 6);
                    if (c == 0) bar_arrive(5, 256); else if (tile < 15) bar_arrive(6, 256);
                    const cplx zero = {0.f, 0.f};
                    float Gx[16], Gy[16];
                    #pragma unroll
                    for (int q = 0; q < 16; q++) {
                        cplx e0 = {acc[4 * q], acc[4 * q + 2]}, e1 = {acc[4 * q + 1], acc[4 * q + 3]};
                        cplx a1 = cmadd(l1, e0, e1);
                        cplx x;
                        x.x = __shfl_up_sync(0xffffffffu, a1.x, 1, 4); x.y = __shfl_up_sync(0xffffffffu, a1.y, 1, 4);
                        if (t < 1) x = zero;
                        a1 = cmadd(l2, x, a1);
                        acc[4 * q + 1] = a1.x; acc[4 * q + 3] = a1.y;
                    }
                    #pragma unroll
                    for (int q = 0; q < 16; q++) {
                        cplx a1 = {acc[4 * q + 1], acc[4 * q + 3]}, x;
                        x.x = __shfl_up_sync(0xffffffffu, a1.x, 2, 4); x.y = __shfl_up_sync(0xffffffffu, a1.y, 2, 4);
                        if (t < 2) x = zero;
                        a1 = cmadd(l4, x, a1);
                        acc[4 * q + 1] = a1.x; acc[4 * q + 3] = a1.y;
                    }
                    #pragma unroll
                    for (int q = 0; q < 16; q++) {
                        cplx a1 = {acc[4 * q + 1], acc[4 * q + 3]}, e0 = {acc[4 * q], acc[4 * q + 2]}, x;
                        x.x = __shfl_up_sync(0xffffffffu, a1.x, 1, 4); x.y = __shfl_up_sync(0xffffffffu, a1.y, 1, 4);
                        if (t < 1) x = zero;
                        e0 = cmadd(l1, x, e0);
                        acc[4 * q] = e0.x; acc[4 * q + 2] = e0.y;
                        Gx[q] = __shfl_sync(0xffffffffu, a1.x, 3, 4); Gy[q] = __shfl_sync(0xffffffffu, a1.y, 3, 4);
                    }
                    #pragma unroll
                    for (int q2 = 0; q2 < 8; q2++) {
                        uint32_t pr[2], pi[2];
                        #pragma unroll
                        for (int e = 0; e < 2; e++) {
                            const int q = 2 * q2 + e;
                            cplx a0 = {acc[4 * q], acc[4 * q + 2]}, a1 = {acc[4 * q + 1], acc[4 * q + 3]}, G = {Gx[q], Gy[q]};
                            cplx h0 = cmadd(pw0, carry, a0), h1 = cmadd(pw1, carry, a1);
                            carry = cmadd(l8, carry, G);
                            h0 = cmadd(coef, h0, zero); h1 = cmadd(coef, h1, zero);
                            pr[e] = pack_bf16(h0.x, h1.x); pi[e] = pack_bf16(h0.y, h1.y);
                        }
                        const int src0 = (lane & 28) | (2 * (t & 1)), src1 = src0 + 1;
                        const uint32_t r00 = __shfl_sync(0xffffffffu, pr[0], src0), r01 = __shfl_sync(0xffffffffu, pr[0], src1);
                        const uint32_t r10 = __shfl_sync(0xffffffffu, pr[1], src0), r11 = __shfl_sync(0xffffffffu, pr[1], src1);
                        const uint32_t i00 = __shfl_sync(0xffffffffu, pi[0], src0), i01 = __shfl_sync(0xffffffffu, pi[0], src1);
                        const uint32_t i10 = __shfl_sync(0xffffffffu, pi[1], src0), i11 = __shfl_sync(0xffffffffu, pi[1], src1);
                        const int tok = tile * 128 + 16 * q2 + 8 * (t >> 1) + 4 * (t & 1);
                        *reinterpret_cast<uint2*>(hre + tok) = (t >> 1) ? make_uint2(r10, r11) : make_uint2(r00, r01);
                        *reinterpret_cast<uint2*>(him + tok) = (t >> 1) ? make_uint2(i10, i11) : make_uint2(i00, i01);
                    }
                    if (c == 0) bar_arrive(3, 160); else bar_arrive(4, 160);
                }
            } else if (type == 1) {
                mbar_wait(mbR, rph); rph ^= 1;
                const int h0 = b >= 16 ? b - 16 : b, nhd = b >= 16 ? 2 : 1;
                #pragma unroll 1
                for (int hh = 0; hh < nhd; hh++) {
                float S[32], SM[8];
                #pragma unroll
                for (int i = 0; i < 32; i++) S[i] = 0.f;
                #pragma unroll
                for (int i = 0; i < 8; i++) SM[i] = 0.f;
                uint32_t af[2][14][4];
                const uint64_t dx = opaque64(desc_sw128(sb + BK_R0 + c * 8192)), dm = opaque64(desc_sw128(sb + BK_RM + c * 2048));
                #pragma unroll
                for (int nh = 0; nh < 2; nh++) {
                    float T[112];
                    #pragma unroll
                    for (int i = 0; i < 112; i++) T[i] = 0.f;
                    #pragma unroll 1
                    for (int kb = 0; kb < 7; kb++) {
                        mbar_wait(mbF + 8 * st, ph);
                        const uint64_t da = opaque64(desc_sw128(sb + BK_R0 + kb * 16384 + c * 8192)), db = opaque64(desc_sw128(sb + BK_R1 + st * 28672));
                        wg_fence();
                        #pragma unroll
                        for (int ks = 0; ks < 4; ks++) wg_n224_ss(T, da + 2 * ks, db + 2 * ks, 1);
                        wg_commit();
                        wg_wait1();
                        if (kb > 0 && lane == 0) mbar_arrive(mbE + 8 * (st == 0 ? 2 : st - 1));
                        if (++st == 3) { st = 0; ph ^= 1; }
                    }
                    wg_wait0();
                    if (lane == 0) mbar_arrive(mbE + 8 * (st == 0 ? 2 : st - 1));
                    #pragma unroll
                    for (int k = 0; k < 14; k++) {
                        af[nh][k][0] = pack_bf16(T[8 * k], T[8 * k + 1]); af[nh][k][1] = pack_bf16(T[8 * k + 2], T[8 * k + 3]);
                        af[nh][k][2] = pack_bf16(T[8 * k + 4], T[8 * k + 5]); af[nh][k][3] = pack_bf16(T[8 * k + 6], T[8 * k + 7]);
                    }
                    wg_fence();
                    #pragma unroll
                    for (int k = 0; k < 14; k++) {
                        const int dp = nh * 224 + 16 * k;
                        wg_n64_rs(S, af[nh][k][0], af[nh][k][1], af[nh][k][2], af[nh][k][3], dx + (uint64_t)(((dp >> 6) * 16384 + (dp & 63) * 2) >> 4), 1);
                    }
                    wg_commit();
                    if (nh == 0) wg_wait0();
                }
                if (hh == 0) { mbar_wait(mbM, mph); mph ^= 1; }
                wg_fence();
                #pragma unroll
                for (int nh = 0; nh < 2; nh++)
                    #pragma unroll
                    for (int k = 0; k < 14; k++) {
                        const int dp = nh * 224 + 16 * k;
                        wg_n16_rs(SM, af[nh][k][0], af[nh][k][1], af[nh][k][2], af[nh][k][3], dm + (uint64_t)(((dp >> 6) * 4096 + (dp & 63) * 2) >> 4), 1);
                    }
                wg_commit();
                wg_wait0();
                const int sl = j >> 1;
                const int row0 = 16 * (j & 1) + g;
                float v[2][10];
                #pragma unroll
                for (int q = 0; q < 4; q++) {
                    float s0 = sl ? S[16 + 4 * q] : S[4 * q], s1 = sl ? S[16 + 4 * q + 1] : S[4 * q + 1];
                    float s2 = sl ? S[16 + 4 * q + 2] : S[4 * q + 2], s3 = sl ? S[16 + 4 * q + 3] : S[4 * q + 3];
                    const int k0 = 8 * q + 2 * t;
                    v[0][2 + 2 * q] = k0 <= row0 ? s0 : -INFINITY; v[0][3 + 2 * q] = k0 + 1 <= row0 ? s1 : -INFINITY;
                    v[1][2 + 2 * q] = k0 <= row0 + 8 ? s2 : -INFINITY; v[1][3 + 2 * q] = k0 + 1 <= row0 + 8 ? s3 : -INFINITY;
                }
                v[0][0] = sl ? SM[4] : SM[0]; v[0][1] = sl ? SM[5] : SM[1]; v[1][0] = sl ? SM[6] : SM[2]; v[1][1] = sl ? SM[7] : SM[3];
                uint32_t Pk[2][5];
                #pragma unroll
                for (int rr = 0; rr < 2; rr++) {
                    float mx = v[rr][0];
                    #pragma unroll
                    for (int k = 1; k < 10; k++) mx = fmaxf(mx, v[rr][k]);
                    mx = fmaxf(mx, __shfl_xor_sync(0xffffffffu, mx, 1));
                    mx = fmaxf(mx, __shfl_xor_sync(0xffffffffu, mx, 2));
                    const float ml = mx * LOG2E;
                    float sum = 0.f;
                    #pragma unroll
                    for (int k = 0; k < 10; k++) { v[rr][k] = ex2(fmaf(v[rr][k], LOG2E, -ml)); sum += v[rr][k]; }
                    sum += __shfl_xor_sync(0xffffffffu, sum, 1);
                    sum += __shfl_xor_sync(0xffffffffu, sum, 2);
                    const float inv = __fdividef(1.f, sum);
                    #pragma unroll
                    for (int k = 0; k < 5; k++) Pk[rr][k] = pack_bf16(v[rr][2 * k] * inv, v[rr][2 * k + 1] * inv);
                }
                const int s = a * 4 + c * 2 + sl;
                uint2* pf = g_pfrag + ((size_t)((s * 2 + (j & 1)) * NH + h0 + hh) * 5) * 32 + lane;
                #pragma unroll
                for (int k = 0; k < 5; k++) pf[k * 32] = make_uint2(Pk[0][k], Pk[1][k]);
                __syncwarp();
                if (lane == 0) signal_count(&g_cnt_tx[s]);
                }
            } else if (type == 2) {
                float acc[112];
                #pragma unroll
                for (int i = 0; i < 112; i++) acc[i] = 0.f;
                #pragma unroll 1
                for (int q = 0; q < 7; q++) {
                    mbar_wait(mbF + 8 * st, ph);
                    const uint64_t da = opaque64(desc_sw128(sb + BK_R0 + q * 16384 + c * 8192)), db = opaque64(desc_sw128(sb + BK_R1 + st * 28672));
                    wg_fence();
                    #pragma unroll
                    for (int ks = 0; ks < 4; ks++) wg_n224_ss_ta(acc, da + 128 * ks, db + 2 * ks, 1);
                    wg_commit();
                    wg_wait1();
                    if (q > 0 && lane == 0) mbar_arrive(mbE + 8 * (st == 0 ? 2 : st - 1));
                    if (++st == 3) { st = 0; ph ^= 1; }
                }
                #pragma unroll 1
                for (int q = 0; q < 7; q++) {
                    mbar_wait(mbF + 8 * st, ph);
                    const uint64_t da = opaque64(desc_sw128(sb + BK_R0 + q * 16384 + c * 8192)), db = opaque64(desc_sw128(sb + BK_R1 + st * 28672));
                    wg_fence();
                    #pragma unroll
                    for (int ks = 0; ks < 4; ks++) wg_n224_ss_ta_neg(acc, da + 128 * ks, db + 2 * ks, 1);
                    wg_commit();
                    wg_wait1();
                    if (lane == 0) mbar_arrive(mbE + 8 * (st == 0 ? 2 : st - 1));
                    if (++st == 3) { st = 0; ph ^= 1; }
                }
                wg_wait0();
                if (lane == 0) mbar_arrive(mbE + 8 * (st == 0 ? 2 : st - 1));
                #pragma unroll
                for (int rr = 0; rr < 2; rr++) {
                    const int tok = a * 128 + c * 64 + j * 16 + g + 8 * rr;
                    const float gt = g_gate[tok];
                    const uint32_t* xp = reinterpret_cast<const uint32_t*>(P.Ax + (size_t)tok * D + b * 224 + 2 * t);
                    const uint32_t* dp = reinterpret_cast<const uint32_t*>(P.Dskip + b * 224 + 2 * t);
                    float2* op = reinterpret_cast<float2*>(P.out + (size_t)tok * D + b * 224 + 2 * t);
                    #pragma unroll
                    for (int q = 0; q < 28; q++) {
                        const uint32_t x = __ldg(xp + 4 * q), d = __ldg(dp + 4 * q);
                        float2 o;
                        o.x = gt * (2.f * acc[4 * q + 2 * rr] + bfr(bf_lo(x) * bf_lo(d)));
                        o.y = gt * (2.f * acc[4 * q + 2 * rr + 1] + bfr(bf_hi(x) * bf_hi(d)));
                        op[4 * q] = o;
                    }
                }
                __syncwarp();
                if (lane == 0) signal_count(&g_cnt_ga[a]);
            } else {
                mbar_wait(mbR, rph); rph ^= 1;
                if (cw < 7) {
                    const int s = a, mt = b * 7 + cw;
                    const uint32_t pbase = sb + BK_R0 + lane * 8, vbase = sb + BK_R0 + 40960 + cw * 20480 + lane * 8;
                    float acc[2][2][4];
                    #pragma unroll
                    for (int x0 = 0; x0 < 2; x0++) for (int x1 = 0; x1 < 2; x1++) for (int x3 = 0; x3 < 4; x3++) acc[x0][x1][x3] = 0.f;
                    float2 ov[2][2][2];
                    float omg[2][2];
                    #pragma unroll
                    for (int tm = 0; tm < 2; tm++)
                        #pragma unroll
                        for (int rr = 0; rr < 2; rr++) {
                            const int tok = s * 32 + tm * 16 + g + 8 * rr;
                            omg[tm][rr] = g_omg[tok];
                            #pragma unroll
                            for (int hf = 0; hf < 2; hf++) ov[tm][rr][hf] = __ldcg(reinterpret_cast<const float2*>(P.out + (size_t)tok * D + mt * 16 + hf * 8 + 2 * t));
                        }
                    mbar_wait(mbF + 192 + 8 * cw, fph);
                    #pragma unroll 8
                    for (int i = 0; i < 40; i++) {
                        const uint2 pa0 = ls64(pbase + (2 * i) * 256), pb0 = ls64(pbase + (2 * i + 1) * 256), pa1 = ls64(pbase + (80 + 2 * i) * 256), pb1 = ls64(pbase + (81 + 2 * i) * 256);
                        const uint2 va = ls64(vbase + (2 * i) * 256), vb = ls64(vbase + (2 * i + 1) * 256);
                        mma_nv(acc[0][0], pa0.x, pa0.y, pb0.x, pb0.y, va.x, vb.x);
                        mma_nv(acc[0][1], pa0.x, pa0.y, pb0.x, pb0.y, va.y, vb.y);
                        mma_nv(acc[1][0], pa1.x, pa1.y, pb1.x, pb1.y, va.x, vb.x);
                        mma_nv(acc[1][1], pa1.x, pa1.y, pb1.x, pb1.y, va.y, vb.y);
                    }
                    #pragma unroll
                    for (int tm = 0; tm < 2; tm++)
                        #pragma unroll
                        for (int rr = 0; rr < 2; rr++) {
                            const int tok = s * 32 + tm * 16 + g + 8 * rr;
                            #pragma unroll
                            for (int hf = 0; hf < 2; hf++) {
                                float2 o = ov[tm][rr][hf];
                                o.x += bfr(omg[tm][rr] * bfr(acc[tm][hf][2 * rr])); o.y += bfr(omg[tm][rr] * bfr(acc[tm][hf][2 * rr + 1]));
                                *reinterpret_cast<float2*>(P.out + (size_t)tok * D + mt * 16 + hf * 8 + 2 * t) = o;
                            }
                        }
                }
                fph ^= 1;
            }
        }
    }
}
typedef CUresult (*EncodeFn)(CUtensorMap*, CUtensorMapDataType, cuuint32_t, void*, const cuuint64_t*, const cuuint64_t*, const cuuint32_t*, const cuuint32_t*,
                             CUtensorMapInterleave, CUtensorMapSwizzle, CUtensorMapL2promotion, CUtensorMapFloatOOBfill);
static EncodeFn g_enc = nullptr;
static void make_map2d(CUtensorMap* m, const void* ptr, uint64_t cols, uint64_t rows, uint32_t bcols, uint32_t brows) {
    cuuint64_t gd[2] = {cols, rows}; cuuint64_t gs[1] = {cols * 2}; cuuint32_t bd[2] = {bcols, brows}; cuuint32_t es[2] = {1, 1};
    g_enc(m, CU_TENSOR_MAP_DATA_TYPE_BFLOAT16, 2, const_cast<void*>(ptr), gd, gs, bd, es, CU_TENSOR_MAP_INTERLEAVE_NONE, CU_TENSOR_MAP_SWIZZLE_128B,
          CU_TENSOR_MAP_L2_PROMOTION_L2_256B, CU_TENSOR_MAP_FLOAT_OOB_FILL_NONE);
}
struct Maps { CUtensorMap Xp, AtA, AtB, AtS, Wk, Wq, Wv, Wo, Xc, X128, Mem, At, Bre, Bim, Ax, H, Cre, Cim; };
static Maps g_maps;
static const void* g_map_key[17];
#define CHAIN_BACKOFF 1100

extern "C" void kernel_launch(void* const* d_in, const int* in_sizes, int n_in, void* d_out, int out_size)
{
    const bf16* Ax = (const bf16*)d_in[0];
    const bf16* Lre = (const bf16*)d_in[1]; const bf16* Lim = (const bf16*)d_in[2];
    const bf16* Bre = (const bf16*)d_in[3]; const bf16* Bim = (const bf16*)d_in[4];
    const bf16* Cre = (const bf16*)d_in[5]; const bf16* Cim = (const bf16*)d_in[6];
    const bf16* logdt = (const bf16*)d_in[7]; const bf16* Dskip = (const bf16*)d_in[8];
    const bf16* Bx = (const bf16*)d_in[0];
    const bf16* mem0 = (const bf16*)d_in[10];
    const bf16* Wq = (const bf16*)d_in[11]; const bf16* Wk = (const bf16*)d_in[12];
    const bf16* Wv = (const bf16*)d_in[13]; const bf16* Wo = (const bf16*)d_in[14];
    const bf16* gate_w = (const bf16*)d_in[16];
    float* out = (float*)d_out;
    cudaStream_t st = cudaStreamPerThread;

    bool need = g_enc == nullptr;
    for (int i = 0; i < 17 && i < n_in; i++) if (g_map_key[i] != d_in[i]) need = true;
    if (need) {
        if (!g_enc) {
            void* fn = nullptr; cudaDriverEntryPointQueryResult qr;
            cudaGetDriverEntryPoint("cuTensorMapEncodeTiled", &fn, cudaEnableDefault, &qr);
            g_enc = (EncodeFn)fn;
            cudaFuncSetAttribute(prep_kernel, cudaFuncAttributeMaxDynamicSharedMemorySize, (int)PREP_SMEM);
            cudaFuncSetAttribute(chain_kernel, cudaFuncAttributeMaxDynamicSharedMemorySize, (int)CHAIN_SMEM);
            cudaFuncSetAttribute(bulk_kernel, cudaFuncAttributeMaxDynamicSharedMemorySize, (int)BULK_SMEM);
        }
        for (int i = 0; i < 17 && i < n_in; i++) g_map_key[i] = d_in[i];
        void *pAt, *pMem, *pH;
        cudaGetSymbolAddress(&pAt, g_At); cudaGetSymbolAddress(&pMem, g_mem); cudaGetSymbolAddress(&pH, g_hT);
        make_map2d(&g_maps.Wk, Wk, 4096, 448, 64, 64);
        make_map2d(&g_maps.Wq, Wq, 4096, 448, 64, 224);
        make_map2d(&g_maps.Wv, Wv, 4096, 448, 64, 224);
        make_map2d(&g_maps.Wo, Wo, 448, 4096, 64, 64);
        make_map2d(&g_maps.X128, Bx, 448, 2048, 64, 128);
        make_map2d(&g_maps.Mem, pMem, 448, 512, 64, 32);
        make_map2d(&g_maps.At, pAt, 448, 7168, 64, 224);
        {
            cuuint64_t gd[2] = {448, 7168}; cuuint64_t gs[1] = {896}; cuuint32_t bd[2] = {224, 64}; cuuint32_t es[2] = {1, 1};
            g_enc(&g_maps.AtS, CU_TENSOR_MAP_DATA_TYPE_BFLOAT16, 2, pAt, gd, gs, bd, es, CU_TENSOR_MAP_INTERLEAVE_NONE, CU_TENSOR_MAP_SWIZZLE_NONE,
                  CU_TENSOR_MAP_L2_PROMOTION_NONE, CU_TENSOR_MAP_FLOAT_OOB_FILL_NONE);
        }
        make_map2d(&g_maps.AtA, pAt, 448, 7168, 64, 64);
        {
            cuuint64_t gd[2] = {448, 7168}; cuuint64_t gs[1] = {896}; cuuint32_t bd[2] = {16, 224}; cuuint32_t es[2] = {1, 1};
            g_enc(&g_maps.AtB, CU_TENSOR_MAP_DATA_TYPE_BFLOAT16, 2, pAt, gd, gs, bd, es, CU_TENSOR_MAP_INTERLEAVE_NONE, CU_TENSOR_MAP_SWIZZLE_32B,
                  CU_TENSOR_MAP_L2_PROMOTION_NONE, CU_TENSOR_MAP_FLOAT_OOB_FILL_NONE);
            cuuint64_t gd3[3] = {64, 2048, 7}; cuuint64_t gs3[2] = {896, 128}; cuuint32_t bd3[3] = {64, 64, 1}; cuuint32_t es3[3] = {1, 1, 1};
            g_enc(&g_maps.Xp, CU_TENSOR_MAP_DATA_TYPE_BFLOAT16, 3, const_cast<bf16*>(Bx), gd3, gs3, bd3, es3, CU_TENSOR_MAP_INTERLEAVE_NONE, CU_TENSOR_MAP_SWIZZLE_128B,
                  CU_TENSOR_MAP_L2_PROMOTION_L2_256B, CU_TENSOR_MAP_FLOAT_OOB_FILL_NONE);
        }
        make_map2d(&g_maps.Bre, Bre, 448, 448, 64, 8);
        make_map2d(&g_maps.Bim, Bim, 448, 448, 64, 8);
        make_map2d(&g_maps.Ax, Ax, 448, 2048, 64, 128);
        make_map2d(&g_maps.H, pH, 2048, 896, 64, 64);
        make_map2d(&g_maps.Cre, Cre, 448, 448, 64, 224);
        make_map2d(&g_maps.Cim, Cim, 448, 448, 64, 224);
        {
            cuuint64_t gd[3] = {64, 2048, 7}; cuuint64_t gs[2] = {896, 128}; cuuint32_t bd[3] = {64, 32, 1}; cuuint32_t es[3] = {1, 1, 1};
            g_enc(&g_maps.Xc, CU_TENSOR_MAP_DATA_TYPE_BFLOAT16, 3, const_cast<bf16*>(Bx), gd, gs, bd, es, CU_TENSOR_MAP_INTERLEAVE_NONE, CU_TENSOR_MAP_SWIZZLE_128B,
                  CU_TENSOR_MAP_L2_PROMOTION_L2_256B, CU_TENSOR_MAP_FLOAT_OOB_FILL_NONE);
        }
    }
    (void)in_sizes; (void)out_size;

    prep_kernel<<<PREP_ITEMS, PREP_THREADS, PREP_SMEM, st>>>(g_maps.Wk, g_maps.Wq, g_maps.Wv, g_maps.Wo, g_maps.AtS, Ax, gate_w, mem0, Wq, Wk, Wv, Wo);
    {
        cudaLaunchConfig_t cfg = {};
        cfg.blockDim = dim3(CHAIN_THREADS); cfg.dynamicSmemBytes = CHAIN_SMEM; cfg.gridDim = dim3(CL * NH); cfg.stream = st;
        cudaLaunchAttribute at[2]; at[0].id = cudaLaunchAttributeClusterDimension; at[0].val.clusterDim.x = CL; at[0].val.clusterDim.y = 1; at[0].val.clusterDim.z = 1;
        at[1].id = cudaLaunchAttributeProgrammaticStreamSerialization; at[1].val.programmaticStreamSerializationAllowed = 1;
        cfg.attrs = at; cfg.numAttrs = 2;
        cudaLaunchKernelEx(&cfg, chain_kernel, g_maps.Xc, mem0, (int)CHAIN_BACKOFF);
    }
    {
        BulkParams P;
        P.X128 = g_maps.X128; P.Mem = g_maps.Mem; P.At = g_maps.At; P.Bre = g_maps.Bre; P.Bim = g_maps.Bim; P.H = g_maps.H; P.Cre = g_maps.Cre; P.Cim = g_maps.Cim;
        P.Ax = Ax; P.Lre = Lre; P.Lim = Lim; P.logdt = logdt; P.Dskip = Dskip; P.out = out;
        cudaLaunchConfig_t cfg = {};
        cfg.blockDim = dim3(BULK_THREADS); cfg.dynamicSmemBytes = BULK_SMEM; cfg.gridDim = dim3(132); cfg.stream = st;
        cudaLaunchAttribute at[1]; at[0].id = cudaLaunchAttributeProgrammaticStreamSerialization; at[0].val.programmaticStreamSerializationAllowed = 1;
        cfg.attrs = at; cfg.numAttrs = 1;
        cudaLaunchKernelEx(&cfg, bulk_kernel, P);
    }
}
```
